```python
import torch

def _softmax(x, axis=-1):
    return torch.softmax(x, dim=axis)

def _gelu(x):
    return torch.nn.functional.gelu(x, approximate='tanh')

def _silu(x):
    return torch.nn.functional.silu(x)

def _sigmoid(x):
    return torch.sigmoid(x)

def _layernorm(x, axis=-1, eps=1e-05):
    m = x.mean(dim=axis, keepdim=True)
    v = x.var(dim=axis, keepdim=True, unbiased=False)
    return (x - m) / torch.sqrt(v + eps)

def _scatter_add(tgt, idx, src, axis=0):
    return tgt.clone().index_add_(axis, idx, src)

def _segment_sum(src, seg, n):
    out = torch.zeros((n,) + src.shape[1:], dtype=src.dtype)
    return out.index_add_(0, seg, src)

def _pad(x, pw):
    flat = tuple((v for pair in reversed(pw) for v in pair))
    return torch.nn.functional.pad(x, flat)
kernel_name = 'adaLN_cond__sliding_block__moe_arch_mod__prompt'

def setup_inputs():

    _w = lambda a: (lambda t: t.to(torch.bfloat16) if t.is_floating_point() else t)(torch.as_tensor(a))

    def _A_setup():
        B, S, D = (1, 2048, 640)
        return {'x': _w((lambda *s: torch.randn(*s, dtype=torch.bfloat16) * 0.05)(B, S, D)), 'wqkv': _w((lambda *s: torch.randn(*s, dtype=torch.bfloat16) * 0.05)(D, 3 * D)), 'wo': _w((lambda *s: torch.randn(*s, dtype=torch.bfloat16) * 0.05)(D, D))}
    _A_in = _A_setup()

    def _B_setup():
        B, S, D, F, C = (1, 2048, 640, 1536, 2)
        return {'x': _w((lambda *s: torch.randn(*s, dtype=torch.bfloat16) * 0.05)(B, S, D)), 'w_r': _w((lambda *s: torch.randn(*s, dtype=torch.bfloat16) * 0.05)(D)), 'w_gate': _w((lambda *s: torch.randn(*s, dtype=torch.bfloat16) * 0.05)(D, F)), 'w_up': _w((lambda *s: torch.randn(*s, dtype=torch.bfloat16) * 0.05)(D, F)), 'w_down': _w((lambda *s: torch.randn(*s, dtype=torch.bfloat16) * 0.05)(F, D))}
    _B_in = _B_setup()
    return {'A_x': _A_in['x'], 'A_wqkv': _A_in['wqkv'], 'A_wo': _A_in['wo'], 'B_x': _B_in['x'], 'B_w_r': _B_in['w_r'], 'B_w_gate': _B_in['w_gate'], 'B_w_up': _B_in['w_up'], 'B_w_down': _B_in['w_down'], 'c': _w((lambda *s: torch.randn(*s, dtype=torch.bfloat16) * 0.1)(1, 640) * 8.0), 'w_mod': _w((lambda *s: torch.randn(*s, dtype=torch.bfloat16) * 0.1)(640, 6 * 640) * 640 ** (-0.5) * 8.0)}

def reference(A_x, A_wqkv, A_wo, B_x, B_w_r, B_w_gate, B_w_up, B_w_down, c, w_mod):

    def _A_ref(x, wqkv, wo):
        B, S, D = x.shape
        H = 32
        Dh = D // H
        W = 256
        qkv = (lambda x, *d: x.permute(*d))((x @ wqkv).reshape(B, S, 3, H, Dh), 2, 0, 3, 1, 4)
        q, k, v = (qkv[0], qkv[1], qkv[2])
        scores = torch.einsum('bhqd,bhkd->bhqk', q, k) * Dh ** (-0.5)
        idx = torch.arange(S)
        mask = (idx[:, None] - idx[None, :] >= 0) & (idx[:, None] - idx[None, :] < W)
        scores = torch.where(mask[None, None], scores, -1000000000.0)
        p = _softmax(scores, axis=-1)
        o = torch.einsum('bhqk,bhkd->bhqd', p, v)
        return (lambda x, *d: x.permute(*d))(o, 0, 2, 1, 3).reshape(B, S, D) @ wo

    def _B_ref(x, w_r, w_gate, w_up, w_down):
        B, S, D = x.shape
        C = 2
        r = x @ w_r
        idx = torch.argsort(-r, axis=-1)[:, :C]
        idx_e = (lambda x, n, axis: torch.repeat_interleave(x, n, dim=axis))(idx.reshape(B, C, 1), D, axis=2)
        x_sel = (lambda x, i, axis: torch.take_along_dim(x, i, dim=axis))(x, idx_e, axis=1)
        g = _silu(x_sel @ w_gate)
        u = x_sel @ w_up
        y = g * u @ w_down
        r_sel = _sigmoid((lambda x, i, axis: torch.take_along_dim(x, i, dim=axis))(r, idx, axis=1))
        y = y * r_sel.reshape(B, C, 1)
        b_off = (torch.arange(B) * S).reshape(B, 1)
        flat_idx = (idx + b_off).reshape(B * C)
        zero = (x * 0.0).reshape(B * S, D)
        upd = _scatter_add(zero, flat_idx, y.reshape(B * C, D), axis=0)
        return x + upd.reshape(B, S, D)
    x = A_x
    mod = (_silu(c) @ w_mod).reshape(c.shape[0], 6, 1, -1)
    sa, ca, ga, sb, cb, gb = (mod[:, 0].clone(), mod[:, 1].clone(), mod[:, 2].clone(), mod[:, 3].clone(), mod[:, 4].clone(), mod[:, 5].clone())
    h = _layernorm(x, axis=-1) * (1 + ca) + sa
    x = x + ga * _A_ref(h, A_wqkv, A_wo)
    h = _layernorm(x, axis=-1) * (1 + cb) + sb
    x = x + gb * _B_ref(h, B_w_r, B_w_gate, B_w_up, B_w_down)
    return x
```

```cpp
#include <cuda_runtime.h>
#include <cuda.h>
#include <cuda_bf16.h>
#include <stdint.h>

typedef unsigned long long u64;
#define SPIN_LIMIT 1000000
#define MBAR_LIMIT 200000

__device__ unsigned g_epoch;
__device__ __align__(128) uint2 g_mod[1920];
__device__ __align__(128) uint4 g_stat[2048];
__device__ __align__(128) uint4 g_ub[1920];
__device__ __align__(1024) unsigned char g_kv[256 * 22528];
__device__ __align__(1024) unsigned char g_o[256 * 10240];
__device__ __align__(128) unsigned g_kvflag[256 * 8];
__device__ __align__(128) unsigned g_oflag[256 * 8];
__device__ __align__(128) uint4 g_part[16 * 8 * 128];
__device__ __align__(128) uint4 g_keys[8 * 16 * 2];
__device__ __align__(128) uint4 g_h2[16 * 2 * 8 * 20];
__device__ __align__(128) uint4 g_x2[16 * 2 * 8 * 20];
__device__ __align__(128) uint4 g_gu[96 * 8];
#define STAMP(i)

__device__ __forceinline__ uint32_t smem_u32(const void* p) { return (uint32_t)__cvta_generic_to_shared(p); }
__device__ __forceinline__ void mbar_init(uint32_t bar, int cnt) { asm volatile("mbarrier.init.shared::cta.b64 [%0], %1;" ::"r"(bar), "r"(cnt) : "memory"); }
__device__ __forceinline__ void mbar_expect_tx(uint32_t bar, uint32_t bytes) { asm volatile("mbarrier.arrive.expect_tx.shared::cta.b64 _, [%0], %1;" ::"r"(bar), "r"(bytes) : "memory"); }
__device__ __forceinline__ void mbar_arrive(uint32_t bar) { asm volatile("mbarrier.arrive.shared::cta.b64 _, [%0];" ::"r"(bar) : "memory"); }
__device__ __forceinline__ void mbar_wait(uint32_t bar, uint32_t parity) {
  uint32_t ok; int it = 0;
  do {
    asm volatile("{ .reg .pred p; mbarrier.try_wait.parity.shared::cta.b64 p, [%1], %2; selp.u32 %0,1,0,p; }" : "=r"(ok) : "r"(bar), "r"(parity) : "memory");
    if (++it > MBAR_LIMIT) __trap();
  } while (!ok);
}
__device__ __forceinline__ void bar_sync(int id, int n) { asm volatile("bar.sync %0, %1;" ::"r"(id), "r"(n) : "memory"); }
__device__ __forceinline__ bool bar_or(int id, int n, bool v) {
  uint32_t r;
  asm volatile("{ .reg .pred p, q; setp.ne.u32 p, %3, 0; barrier.cta.red.or.aligned.pred q, %1, %2, p; selp.u32 %0,1,0,q; }" : "=r"(r) : "r"(id), "r"(n), "r"((uint32_t)v) : "memory");
  return r != 0;
}
__device__ __forceinline__ void fence_async() { asm volatile("fence.proxy.async;" ::: "memory"); }
__device__ __forceinline__ void fence_async_smem() { asm volatile("fence.proxy.async.shared::cta;" ::: "memory"); }
__device__ __forceinline__ void bulk_load(uint32_t dst, const void* src, uint32_t bytes, uint32_t bar) { asm volatile("cp.async.bulk.shared::cluster.global.mbarrier::complete_tx::bytes [%0], [%1], %2, [%3];" ::"r"(dst), "l"(src), "r"(bytes), "r"(bar) : "memory"); }
__device__ __forceinline__ void bulk_store_wait(void* dst, uint32_t src, uint32_t bytes) {
  asm volatile("cp.async.bulk.global.shared::cta.bulk_group [%0], [%1], %2;" ::"l"(dst), "r"(src), "r"(bytes) : "memory");
  asm volatile("cp.async.bulk.commit_group;" ::: "memory");
  asm volatile("cp.async.bulk.wait_group 0;" ::: "memory");
}
__device__ __forceinline__ void bulk_prefetch(const void* src, uint32_t bytes) { asm volatile("cp.async.bulk.prefetch.L2.global [%0], %1;" ::"l"(src), "r"(bytes) : "memory"); }
__device__ __forceinline__ void tma2d(uint32_t dst, const CUtensorMap* m, int c0, int c1, uint32_t bar) { asm volatile("cp.async.bulk.tensor.2d.shared::cluster.global.mbarrier::complete_tx::bytes [%0], [%1, {%3,%4}], [%2];" ::"r"(dst), "l"(m), "r"(bar), "r"(c0), "r"(c1) : "memory"); }
__device__ __forceinline__ void tma3d(uint32_t dst, const CUtensorMap* m, int c0, int c1, int c2, uint32_t bar) { asm volatile("cp.async.bulk.tensor.3d.shared::cluster.global.mbarrier::complete_tx::bytes [%0], [%1, {%3,%4,%5}], [%2];" ::"r"(dst), "l"(m), "r"(bar), "r"(c0), "r"(c1), "r"(c2) : "memory"); }
__device__ __forceinline__ void wg_fence() { asm volatile("wgmma.fence.sync.aligned;" ::: "memory"); }
__device__ __forceinline__ void wg_commit() { asm volatile("wgmma.commit_group.sync.aligned;" ::: "memory"); }
template <int N> __device__ __forceinline__ void wg_wait() { asm volatile("wgmma.wait_group.sync.aligned %0;" ::"n"(N) : "memory"); }
template <int N> __device__ __forceinline__ void reg_fence(float (&d)[N]) {
#pragma unroll
  for (int i = 0; i < N; i++) asm volatile("" : "+f"(d[i])::"memory");
}
__device__ __forceinline__ u64 dsc(uint32_t lo, uint32_t lbo, uint32_t sbo, uint32_t sw) { return (u64)(lo + ((lbo >> 4) << 16)) | ((u64)((sbo >> 4) | (sw << 30)) << 32); }
__device__ __forceinline__ void ldsm4(uint32_t (&r)[4], uint32_t addr) { asm volatile("ldmatrix.sync.aligned.m8n8.x4.shared.b16 {%0,%1,%2,%3}, [%4];" : "=r"(r[0]), "=r"(r[1]), "=r"(r[2]), "=r"(r[3]) : "r"(addr) : "memory"); }
__device__ __forceinline__ void ldsm4t(uint32_t (&r)[4], uint32_t addr) { asm volatile("ldmatrix.sync.aligned.m8n8.x4.trans.shared.b16 {%0,%1,%2,%3}, [%4];" : "=r"(r[0]), "=r"(r[1]), "=r"(r[2]), "=r"(r[3]) : "r"(addr) : "memory"); }
__device__ __forceinline__ void ldsm2t(uint32_t (&r)[2], uint32_t addr) { asm volatile("ldmatrix.sync.aligned.m8n8.x2.trans.shared.b16 {%0,%1}, [%2];" : "=r"(r[0]), "=r"(r[1]) : "r"(addr) : "memory"); }
__device__ __forceinline__ void stsm4(uint32_t addr, uint32_t a, uint32_t b, uint32_t c, uint32_t d) { asm volatile("stmatrix.sync.aligned.m8n8.x4.shared.b16 [%0], {%1,%2,%3,%4};" ::"r"(addr), "r"(a), "r"(b), "r"(c), "r"(d) : "memory"); }
__device__ __forceinline__ uint4 lds128(uint32_t addr) { uint4 v; asm volatile("ld.shared.v4.u32 {%0,%1,%2,%3}, [%4];" : "=r"(v.x), "=r"(v.y), "=r"(v.z), "=r"(v.w) : "r"(addr) : "memory"); return v; }
__device__ __forceinline__ float4 lds128f(uint32_t addr) { float4 v; asm volatile("ld.shared.v4.f32 {%0,%1,%2,%3}, [%4];" : "=f"(v.x), "=f"(v.y), "=f"(v.z), "=f"(v.w) : "r"(addr) : "memory"); return v; }
__device__ __forceinline__ float2 lds64f(uint32_t addr) { float2 v; asm volatile("ld.shared.v2.f32 {%0,%1}, [%2];" : "=f"(v.x), "=f"(v.y) : "r"(addr) : "memory"); return v; }
__device__ __forceinline__ float lds32f(uint32_t addr) { float v; asm volatile("ld.shared.f32 %0, [%1];" : "=f"(v) : "r"(addr) : "memory"); return v; }
__device__ __forceinline__ uint32_t lds32(uint32_t addr) { uint32_t v; asm volatile("ld.shared.u32 %0, [%1];" : "=r"(v) : "r"(addr) : "memory"); return v; }
__device__ __forceinline__ void sts32(uint32_t addr, uint32_t v) { asm volatile("st.shared.u32 [%0], %1;" ::"r"(addr), "r"(v) : "memory"); }
__device__ __forceinline__ void sts32f(uint32_t addr, float v) { asm volatile("st.shared.f32 [%0], %1;" ::"r"(addr), "f"(v) : "memory"); }
__device__ __forceinline__ void sts64(uint32_t addr, uint32_t a, uint32_t b) { asm volatile("st.shared.v2.u32 [%0], {%1,%2};" ::"r"(addr), "r"(a), "r"(b) : "memory"); }
__device__ __forceinline__ void sts128(uint32_t addr, uint4 v) { asm volatile("st.shared.v4.u32 [%0], {%1,%2,%3,%4};" ::"r"(addr), "r"(v.x), "r"(v.y), "r"(v.z), "r"(v.w) : "memory"); }
__device__ __forceinline__ uint32_t packbf(float lo, float hi) { uint32_t r; asm("cvt.rn.bf16x2.f32 %0, %1, %2;" : "=r"(r) : "f"(hi), "f"(lo)); return r; }
__device__ __forceinline__ float bflo(uint32_t v) { return __uint_as_float(v << 16); }
__device__ __forceinline__ float bfhi(uint32_t v) { return __uint_as_float(v & 0xffff0000u); }
__device__ __forceinline__ float bfround(float x) { return bflo(packbf(x, 0.f)); }
__device__ __forceinline__ uint32_t hmul2(uint32_t a, uint32_t b) { uint32_t r; asm("mul.rn.bf16x2 %0, %1, %2;" : "=r"(r) : "r"(a), "r"(b)); return r; }
__device__ __forceinline__ uint32_t hadd2(uint32_t a, uint32_t b) { uint32_t r; asm("add.rn.bf16x2 %0, %1, %2;" : "=r"(r) : "r"(a), "r"(b)); return r; }
__device__ __forceinline__ float ex2(float x) { float r; asm("ex2.approx.ftz.f32 %0, %1;" : "=f"(r) : "f"(x)); return r; }
__device__ __forceinline__ void mma16(float (&d)[4], uint32_t a0, uint32_t a2, uint32_t b0, uint32_t b1) {
  asm volatile("mma.sync.aligned.m16n8k16.row.col.f32.bf16.bf16.f32 {%0,%1,%2,%3}, {%4,%5,%6,%5}, {%7,%8}, {%0,%1,%2,%3};" : "+f"(d[0]), "+f"(d[1]), "+f"(d[2]), "+f"(d[3]) : "r"(a0), "r"(0u), "r"(a2), "r"(b0), "r"(b1));
}
__device__ __forceinline__ uint4 ldg128(const void* p) { uint4 v; asm volatile("ld.global.nc.L1::no_allocate.v4.u32 {%0,%1,%2,%3}, [%4];" : "=r"(v.x), "=r"(v.y), "=r"(v.z), "=r"(v.w) : "l"(p)); return v; }
__device__ __forceinline__ uint2 ldg64(const void* p) { uint2 v; asm volatile("ld.global.nc.L1::no_allocate.v2.u32 {%0,%1}, [%2];" : "=r"(v.x), "=r"(v.y) : "l"(p)); return v; }
__device__ __forceinline__ void ll_st64(uint2* p, uint32_t a, uint32_t tag) { u64 v = (u64)a | ((u64)tag << 32); asm volatile("st.relaxed.gpu.global.b64 [%0], %1;" ::"l"(p), "l"(v) : "memory"); }
__device__ __forceinline__ void ll_st128(uint4* p, uint32_t a, uint32_t b, uint32_t c, uint32_t tag) {
  asm volatile("{ .reg .b128 v; .reg .b64 lo, hi; mov.b64 lo, {%1,%2}; mov.b64 hi, {%3,%4}; mov.b128 v, {lo,hi}; st.relaxed.gpu.global.b128 [%0], v; }" ::"l"(p), "r"(a), "r"(b), "r"(c), "r"(tag) : "memory");
}
__device__ __forceinline__ uint4 ll_ld128(const uint4* p) {
  uint4 r;
  asm volatile("{ .reg .b128 v; .reg .b64 lo, hi; ld.relaxed.gpu.global.b128 v, [%4]; mov.b128 {lo,hi}, v; mov.b64 {%0,%1}, lo; mov.b64 {%2,%3}, hi; }" : "=r"(r.x), "=r"(r.y), "=r"(r.z), "=r"(r.w) : "l"(p) : "memory");
  return r;
}
__device__ __forceinline__ uint4 ll_wait128(const uint4* p, uint32_t tag) {
  uint4 r; int it = 0;
  do { r = ll_ld128(p); if (++it > SPIN_LIMIT) __trap(); } while (r.w != tag);
  return r;
}
__device__ __forceinline__ uint2 ll_wait64x2(const uint2* p, uint32_t tag) {
  uint4 r; int it = 0;
  do { r = ll_ld128((const uint4*)p); if (++it > SPIN_LIMIT) __trap(); } while (r.y != tag || r.w != tag);
  return make_uint2(r.x, r.z);
}
__device__ __forceinline__ uint32_t ll_wait64(const uint2* p, uint32_t tag) {
  u64 v; int it = 0;
  do { asm volatile("ld.relaxed.gpu.global.b64 %0, [%1];" : "=l"(v) : "l"(p) : "memory"); if (++it > SPIN_LIMIT) __trap(); } while ((uint32_t)(v >> 32) != tag);
  return (uint32_t)v;
}
__device__ __forceinline__ void flag_set(unsigned* p, uint32_t tag) { asm volatile("st.release.gpu.global.u32 [%0], %1;" ::"l"(p), "r"(tag) : "memory"); }
__device__ __forceinline__ uint32_t flag_get(const unsigned* p) { uint32_t v; asm volatile("ld.acquire.gpu.global.u32 %0, [%1];" : "=r"(v) : "l"(p) : "memory"); return v; }
__device__ __forceinline__ uint32_t redux_max(uint32_t v) { uint32_t r; asm volatile("redux.sync.max.u32 %0, %1, 0xffffffff;" : "=r"(r) : "r"(v)); return r; }
__device__ __forceinline__ void cp16(uint32_t dst, const void* src) { asm volatile("cp.async.cg.shared.global [%0], [%1], 16;" ::"r"(dst), "l"(src) : "memory"); }
__device__ __forceinline__ void cp8(uint32_t dst, const void* src) { asm volatile("cp.async.ca.shared.global [%0], [%1], 8;" ::"r"(dst), "l"(src) : "memory"); }
__device__ __forceinline__ void cp_arrive(uint32_t bar) { asm volatile("cp.async.mbarrier.arrive.noinc.shared::cta.b64 [%0];" ::"r"(bar) : "memory"); }
__device__ __forceinline__ void wg_rs192(float (&d)[96], uint32_t a0, uint32_t a1, uint32_t a2, uint32_t a3, uint64_t db){
  asm volatile("{ .reg .pred p; setp.ne.b32 p, 1, 0;\n wgmma.mma_async.sync.aligned.m64n192k16.f32.bf16.bf16 {%0, %1, %2, %3, %4, %5, %6, %7, %8, %9, %10, %11, %12, %13, %14, %15, %16, %17, %18, %19, %20, %21, %22, %23, %24, %25, %26, %27, %28, %29, %30, %31, %32, %33, %34, %35, %36, %37, %38, %39, %40, %41, %42, %43, %44, %45, %46, %47, %48, %49, %50, %51, %52, %53, %54, %55, %56, %57, %58, %59, %60, %61, %62, %63, %64, %65, %66, %67, %68, %69, %70, %71, %72, %73, %74, %75, %76, %77, %78, %79, %80, %81, %82, %83, %84, %85, %86, %87, %88, %89, %90, %91, %92, %93, %94, %95}, {%96,%97,%98,%99}, %100, p, 1, 1, 1; }"
   : "+f"(d[0]), "+f"(d[1]), "+f"(d[2]), "+f"(d[3]), "+f"(d[4]), "+f"(d[5]), "+f"(d[6]), "+f"(d[7]), "+f"(d[8]), "+f"(d[9]), "+f"(d[10]), "+f"(d[11]), "+f"(d[12]), "+f"(d[13]), "+f"(d[14]), "+f"(d[15]), "+f"(d[16]), "+f"(d[17]), "+f"(d[18]), "+f"(d[19]), "+f"(d[20]), "+f"(d[21]), "+f"(d[22]), "+f"(d[23]), "+f"(d[24]), "+f"(d[25]), "+f"(d[26]), "+f"(d[27]), "+f"(d[28]), "+f"(d[29]), "+f"(d[30]), "+f"(d[31]), "+f"(d[32]), "+f"(d[33]), "+f"(d[34]), "+f"(d[35]), "+f"(d[36]), "+f"(d[37]), "+f"(d[38]), "+f"(d[39]), "+f"(d[40]), "+f"(d[41]), "+f"(d[42]), "+f"(d[43]), "+f"(d[44]), "+f"(d[45]), "+f"(d[46]), "+f"(d[47]), "+f"(d[48]), "+f"(d[49]), "+f"(d[50]), "+f"(d[51]), "+f"(d[52]), "+f"(d[53]), "+f"(d[54]), "+f"(d[55]), "+f"(d[56]), "+f"(d[57]), "+f"(d[58]), "+f"(d[59]), "+f"(d[60]), "+f"(d[61]), "+f"(d[62]), "+f"(d[63]), "+f"(d[64]), "+f"(d[65]), "+f"(d[66]), "+f"(d[67]), "+f"(d[68]), "+f"(d[69]), "+f"(d[70]), "+f"(d[71]), "+f"(d[72]), "+f"(d[73]), "+f"(d[74]), "+f"(d[75]), "+f"(d[76]), "+f"(d[77]), "+f"(d[78]), "+f"(d[79]), "+f"(d[80]), "+f"(d[81]), "+f"(d[82]), "+f"(d[83]), "+f"(d[84]), "+f"(d[85]), "+f"(d[86]), "+f"(d[87]), "+f"(d[88]), "+f"(d[89]), "+f"(d[90]), "+f"(d[91]), "+f"(d[92]), "+f"(d[93]), "+f"(d[94]), "+f"(d[95]) : "r"(a0),"r"(a1),"r"(a2),"r"(a3),"l"(db));
}
__device__ __forceinline__ void wg_rs48(float (&d)[24], uint32_t a0, uint32_t a1, uint32_t a2, uint32_t a3, uint64_t db){
  asm volatile("{ .reg .pred p; setp.ne.b32 p, 1, 0;\n wgmma.mma_async.sync.aligned.m64n48k16.f32.bf16.bf16 {%0, %1, %2, %3, %4, %5, %6, %7, %8, %9, %10, %11, %12, %13, %14, %15, %16, %17, %18, %19, %20, %21, %22, %23}, {%24,%25,%26,%27}, %28, p, 1, 1, 1; }"
   : "+f"(d[0]), "+f"(d[1]), "+f"(d[2]), "+f"(d[3]), "+f"(d[4]), "+f"(d[5]), "+f"(d[6]), "+f"(d[7]), "+f"(d[8]), "+f"(d[9]), "+f"(d[10]), "+f"(d[11]), "+f"(d[12]), "+f"(d[13]), "+f"(d[14]), "+f"(d[15]), "+f"(d[16]), "+f"(d[17]), "+f"(d[18]), "+f"(d[19]), "+f"(d[20]), "+f"(d[21]), "+f"(d[22]), "+f"(d[23]) : "r"(a0),"r"(a1),"r"(a2),"r"(a3),"l"(db));
}
__device__ __forceinline__ void wg_rs64z(float (&d)[32], uint32_t a0, uint32_t a1, uint32_t a2, uint32_t a3, uint64_t db){
  asm volatile("{ .reg .pred p; setp.ne.b32 p, 0, 0;\n wgmma.mma_async.sync.aligned.m64n64k16.f32.bf16.bf16 {%0, %1, %2, %3, %4, %5, %6, %7, %8, %9, %10, %11, %12, %13, %14, %15, %16, %17, %18, %19, %20, %21, %22, %23, %24, %25, %26, %27, %28, %29, %30, %31}, {%32,%33,%34,%35}, %36, p, 1, 1, 0; }"
   : "=f"(d[0]), "=f"(d[1]), "=f"(d[2]), "=f"(d[3]), "=f"(d[4]), "=f"(d[5]), "=f"(d[6]), "=f"(d[7]), "=f"(d[8]), "=f"(d[9]), "=f"(d[10]), "=f"(d[11]), "=f"(d[12]), "=f"(d[13]), "=f"(d[14]), "=f"(d[15]), "=f"(d[16]), "=f"(d[17]), "=f"(d[18]), "=f"(d[19]), "=f"(d[20]), "=f"(d[21]), "=f"(d[22]), "=f"(d[23]), "=f"(d[24]), "=f"(d[25]), "=f"(d[26]), "=f"(d[27]), "=f"(d[28]), "=f"(d[29]), "=f"(d[30]), "=f"(d[31]) : "r"(a0),"r"(a1),"r"(a2),"r"(a3),"l"(db));
}
__device__ __forceinline__ void wg_rs64(float (&d)[32], uint32_t a0, uint32_t a1, uint32_t a2, uint32_t a3, uint64_t db){
  asm volatile("{ .reg .pred p; setp.ne.b32 p, 1, 0;\n wgmma.mma_async.sync.aligned.m64n64k16.f32.bf16.bf16 {%0, %1, %2, %3, %4, %5, %6, %7, %8, %9, %10, %11, %12, %13, %14, %15, %16, %17, %18, %19, %20, %21, %22, %23, %24, %25, %26, %27, %28, %29, %30, %31}, {%32,%33,%34,%35}, %36, p, 1, 1, 0; }"
   : "+f"(d[0]), "+f"(d[1]), "+f"(d[2]), "+f"(d[3]), "+f"(d[4]), "+f"(d[5]), "+f"(d[6]), "+f"(d[7]), "+f"(d[8]), "+f"(d[9]), "+f"(d[10]), "+f"(d[11]), "+f"(d[12]), "+f"(d[13]), "+f"(d[14]), "+f"(d[15]), "+f"(d[16]), "+f"(d[17]), "+f"(d[18]), "+f"(d[19]), "+f"(d[20]), "+f"(d[21]), "+f"(d[22]), "+f"(d[23]), "+f"(d[24]), "+f"(d[25]), "+f"(d[26]), "+f"(d[27]), "+f"(d[28]), "+f"(d[29]), "+f"(d[30]), "+f"(d[31]) : "r"(a0),"r"(a1),"r"(a2),"r"(a3),"l"(db));
}
__device__ __forceinline__ void wg_rs24(float (&d)[12], uint32_t a0, uint32_t a1, uint32_t a2, uint32_t a3, uint64_t db){
  asm volatile("{ .reg .pred p; setp.ne.b32 p, 1, 0;\n wgmma.mma_async.sync.aligned.m64n24k16.f32.bf16.bf16 {%0, %1, %2, %3, %4, %5, %6, %7, %8, %9, %10, %11}, {%12,%13,%14,%15}, %16, p, 1, 1, 1; }"
   : "+f"(d[0]), "+f"(d[1]), "+f"(d[2]), "+f"(d[3]), "+f"(d[4]), "+f"(d[5]), "+f"(d[6]), "+f"(d[7]), "+f"(d[8]), "+f"(d[9]), "+f"(d[10]), "+f"(d[11]) : "r"(a0),"r"(a1),"r"(a2),"r"(a3),"l"(db));
}
__device__ __forceinline__ void wg_ss80(float (&d)[40], uint64_t da, uint64_t db){
  asm volatile("{ .reg .pred p; setp.ne.b32 p, 1, 0;\n wgmma.mma_async.sync.aligned.m64n80k16.f32.bf16.bf16 {%0, %1, %2, %3, %4, %5, %6, %7, %8, %9, %10, %11, %12, %13, %14, %15, %16, %17, %18, %19, %20, %21, %22, %23, %24, %25, %26, %27, %28, %29, %30, %31, %32, %33, %34, %35, %36, %37, %38, %39}, %40, %41, p, 1, 1, 0, 1; }"
   : "+f"(d[0]), "+f"(d[1]), "+f"(d[2]), "+f"(d[3]), "+f"(d[4]), "+f"(d[5]), "+f"(d[6]), "+f"(d[7]), "+f"(d[8]), "+f"(d[9]), "+f"(d[10]), "+f"(d[11]), "+f"(d[12]), "+f"(d[13]), "+f"(d[14]), "+f"(d[15]), "+f"(d[16]), "+f"(d[17]), "+f"(d[18]), "+f"(d[19]), "+f"(d[20]), "+f"(d[21]), "+f"(d[22]), "+f"(d[23]), "+f"(d[24]), "+f"(d[25]), "+f"(d[26]), "+f"(d[27]), "+f"(d[28]), "+f"(d[29]), "+f"(d[30]), "+f"(d[31]), "+f"(d[32]), "+f"(d[33]), "+f"(d[34]), "+f"(d[35]), "+f"(d[36]), "+f"(d[37]), "+f"(d[38]), "+f"(d[39]) : "l"(da),"l"(db));
}
constexpr uint32_t STAGE = 47104, CHB = 22528, GB = 2816;
constexpr uint32_t KVO = 94208, WO = 139264, WO7 = 112640, OST1 = 129024, MOEW = 30720;
constexpr uint32_t TAB1 = 188416, T_C1 = TAB1, T_UB = TAB1 + 1280, T_ST = TAB1 + 3200, T_RED = TAB1 + 4224, T_RED2 = TAB1 + 4736, T_MOD = TAB1 + 5248, T_SIL = TAB1 + 7808;
constexpr uint32_t TAB2 = 228864, T_EA = TAB2, T_EB = TAB2 + 640, T_EC = TAB2 + 1280, T_SC = TAB2 + 1600, T_KEY = TAB2 + 1664, BARS = TAB2 + 1792;
constexpr uint32_t T_OUT = WO, T_MRED = WO + 32768;
constexpr uint32_t SMEM_BYTES = TAB2 + 2304;
enum { B_FULL = 0, B_EMPTY = 4, B_KV = 8, B_PRM1 = 14, B_EPI1 = 15, B_WO = 16, B_OF = 24, B_DONE0 = 38, B_DONE1 = 39, B_DONE5 = 40, B_ATT = 41, B_PRM2 = 42, B_MOEW = 43, B_GEMM = 44, B_NUM = 45 };

struct Params {
  CUtensorMap mx, mw64, mw16, mwo;
  const __nv_bfloat16 *x, *wqkv, *wo, *wr, *wg, *wu, *wd, *c, *wmod;
  __nv_bfloat16* out;
};

__device__ __forceinline__ float silu_f(float v) { return v / (1.f + __expf(-v)); }
__device__ __forceinline__ void fma8(float (&a)[8], uint4 w, float s) {
  a[0] = fmaf(s, bflo(w.x), a[0]); a[1] = fmaf(s, bfhi(w.x), a[1]); a[2] = fmaf(s, bflo(w.y), a[2]); a[3] = fmaf(s, bfhi(w.y), a[3]);
  a[4] = fmaf(s, bflo(w.z), a[4]); a[5] = fmaf(s, bfhi(w.z), a[5]); a[6] = fmaf(s, bflo(w.w), a[6]); a[7] = fmaf(s, bfhi(w.w), a[7]);
}
__device__ __forceinline__ float red8(float (&a)[8], int lane) {
  const bool b1 = lane & 2, b2 = lane & 4, b3 = lane & 8;
  float t[4], u[2];
#pragma unroll
  for (int j = 0; j < 4; j++) { float s = b1 ? a[j] : a[4 + j], k = b1 ? a[4 + j] : a[j]; t[j] = k + __shfl_xor_sync(~0u, s, 2); }
#pragma unroll
  for (int j = 0; j < 2; j++) { float s = b2 ? t[j] : t[2 + j], k = b2 ? t[2 + j] : t[j]; u[j] = k + __shfl_xor_sync(~0u, s, 4); }
  float s = b3 ? u[0] : u[1], k = b3 ? u[1] : u[0];
  k += __shfl_xor_sync(~0u, s, 8);
  return k + __shfl_xor_sync(~0u, k, 16);
}
__device__ __forceinline__ int red8_col(int lane) { return (lane & 1) * 8 + ((lane >> 1) & 1) * 4 + ((lane >> 2) & 1) * 2 + ((lane >> 3) & 1); }

__device__ __forceinline__ void issue_qk(float (&s)[32], const uint32_t (&q)[8], uint32_t cb, int h) {
  const uint32_t pb = cb + (h >> 1) * 88;
  wg_rs64z(s, q[0], q[1], q[2], q[3], dsc(pb + ((h & 1) ? 24 : 0), 128, GB, 0));
  wg_rs64(s, q[4], q[5], q[6], q[7], dsc(pb + 16, 640, GB, 0));
}
__device__ __forceinline__ void issue_pv1(float (&o)[12], const uint32_t (&p)[16], uint32_t cb, int h, int b) {
  wg_rs24(o, p[4 * b], p[4 * b + 1], p[4 * b + 2], p[4 * b + 3], dsc(cb + (h >> 1) * 88 + 40 + (h & 1) * 24 + b * (2 * GB / 16), GB, 128, 0));
}
__device__ __forceinline__ uint32_t sortable(float r) { uint32_t u = __float_as_uint(r); return (u & 0x80000000u) ? ~u : (u | 0x80000000u); }
__device__ __forceinline__ float unsortable(uint32_t k) { return __uint_as_float((k & 0x80000000u) ? (k & 0x7fffffffu) : ~k); }
__device__ __forceinline__ void top2(uint32_t a, uint32_t b, uint32_t& k1, uint32_t& k2) {
  k1 = redux_max(max(a, b));
  k2 = redux_max(max(a == k1 ? 0u : a, b == k1 ? 0u : b));
}

__global__ void __launch_bounds__(384, 1) fused_kernel(const __grid_constant__ Params P) {
  extern __shared__ __align__(1024) unsigned char smem_raw[];
  const uint32_t sm = smem_u32(smem_raw);
  const int tid = threadIdx.x, lane = tid & 31;
  const int warp = __shfl_sync(~0u, tid >> 5, 0);
  const int cta = blockIdx.x, m = cta >> 3, g = cta & 7;
  uint32_t tag;
  asm volatile("ld.relaxed.gpu.global.u32 %0, [%1];" : "=r"(tag) : "l"(&g_epoch) : "memory");
  auto bar = [&](int i) { return sm + BARS + 8 * i; };
  if (warp < 8) {
    asm volatile("setmaxnreg.inc.sync.aligned.u32 232;");
    const int wg = warp >> 2, wl = warp & 3, gq = lane >> 2, q4 = lane & 3;
    {
      const int G1 = cta < 40 ? 40 + cta : (cta < 80 ? cta - 40 : cta);
      uint4 w[5]; float sc[5]; uint2 xr[2][5];
#pragma unroll
      for (int i = 0; i < 5; i++) w[i] = ldg128(P.wmod + (size_t)((tid >> 1) + 128 * i) * 3840 + G1 * 16 + (tid & 1) * 8);
#pragma unroll
      for (int i = 0; i < 5; i++) sc[i] = __bfloat162float(P.c[(tid >> 1) + 128 * i]);
#pragma unroll
      for (int r = 0; r < 2; r++)
#pragma unroll
        for (int i = 0; i < 5; i++) xr[r][i] = ldg64(P.x + (size_t)(cta * 16 + warp * 2 + r) * 640 + i * 128 + lane * 4);
      float a[8] = {0.f, 0.f, 0.f, 0.f, 0.f, 0.f, 0.f, 0.f};
#pragma unroll
      for (int i = 0; i < 5; i++) fma8(a, w[i], bfround(silu_f(sc[i])));
      const float v = red8(a, lane);
      if (lane < 16) sts32f(sm + T_RED + warp * 64 + red8_col(lane) * 4, v);
      tag += 1;
      bar_sync(0, 384);
      if (tid < 8) {
        float s0 = 0.f, s1 = 0.f;
#pragma unroll
        for (int w2 = 0; w2 < 8; w2++) { float2 t = lds64f(sm + T_RED + w2 * 64 + tid * 8); s0 += t.x; s1 += t.y; }
        ll_st64(&g_mod[G1 * 8 + tid], packbf(s0, s1), tag);
      }
      float rs[2], nm[2];
#pragma unroll
      for (int r = 0; r < 2; r++) {
        float s = 0.f;
#pragma unroll
        for (int i = 0; i < 5; i++) s += (bflo(xr[r][i].x) + bfhi(xr[r][i].x)) + (bflo(xr[r][i].y) + bfhi(xr[r][i].y));
#pragma unroll
        for (int o = 16; o; o >>= 1) s += __shfl_xor_sync(~0u, s, o);
        const float mean = s * (1.f / 640.f);
        float q = 0.f;
#pragma unroll
        for (int i = 0; i < 5; i++) {
          float d0 = bflo(xr[r][i].x) - mean, d1 = bfhi(xr[r][i].x) - mean, d2 = bflo(xr[r][i].y) - mean, d3 = bfhi(xr[r][i].y) - mean;
          q = fmaf(d0, d0, q); q = fmaf(d1, d1, q); q = fmaf(d2, d2, q); q = fmaf(d3, d3, q);
        }
#pragma unroll
        for (int o = 16; o; o >>= 1) q += __shfl_xor_sync(~0u, q, o);
        rs[r] = rsqrtf(q * (1.f / 640.f) + 1e-5f); nm[r] = -mean * rs[r];
      }
      if (lane < 2) ll_st128(&g_stat[cta * 16 + warp * 2 + lane], __float_as_uint(lane ? rs[1] : rs[0]), __float_as_uint(lane ? nm[1] : nm[0]), 0u, tag);
      STAMP(0);
      if (tid < 160) {
        const uint2 v2 = ll_wait64x2(&g_mod[320 + 2 * tid], tag);
        const int p = 2 * tid;
        const uint32_t ad = sm + T_C1 + ((p & ~15) + (p & 3) * 4 + ((p >> 2) & 3)) * 4;
        sts32(ad, hadd2(v2.x, 0x3f803f80u)); sts32(ad + 16, hadd2(v2.y, 0x3f803f80u));
      }
      bar_sync(1, 256);
      STAMP(1);
    }
    uint32_t q[4][8];
    {
      float d1[96], d2[24];
#pragma unroll
      for (int i = 0; i < 96; i++) d1[i] = 0.f;
#pragma unroll
      for (int i = 0; i < 24; i++) d2[i] = 0.f;
      const uint32_t arow = (warp * 16 + (lane & 15)) * 128, asw = lane & 7, ahi = lane >> 4;
      uint32_t f[2][16];
      auto load_a = [&](uint32_t (&fr)[16], int c) {
        const uint32_t st = sm + (c & 3) * STAGE;
        mbar_wait(bar(B_FULL + (c & 3)), (c >> 2) & 1);
#pragma unroll
        for (int k2 = 0; k2 < 2; k2++) {
          uint32_t r0[4], r1[4];
          ldsm4(r0, st + arow + (((4 * k2 + ahi) ^ asw) << 4));
          ldsm4(r1, st + arow + (((4 * k2 + 2 + ahi) ^ asw) << 4));
          const uint4 cf = lds128(sm + T_C1 + (c * 2 + k2) * 64 + q4 * 16);
          fr[8 * k2 + 0] = hmul2(r0[0], cf.x); fr[8 * k2 + 1] = hmul2(r0[1], cf.x); fr[8 * k2 + 2] = hmul2(r0[2], cf.y); fr[8 * k2 + 3] = hmul2(r0[3], cf.y);
          fr[8 * k2 + 4] = hmul2(r1[0], cf.z); fr[8 * k2 + 5] = hmul2(r1[1], cf.z); fr[8 * k2 + 6] = hmul2(r1[2], cf.w); fr[8 * k2 + 7] = hmul2(r1[3], cf.w);
        }
      };
      auto issue = [&](const uint32_t (&fr)[16], int c) {
        const uint32_t st = (sm + (c & 3) * STAGE) >> 4;
        wg_fence();
#pragma unroll
        for (int ks = 0; ks < 4; ks++) {
          wg_rs192(d1, fr[4 * ks], fr[4 * ks + 1], fr[4 * ks + 2], fr[4 * ks + 3], dsc(st + 1024 + ks * 128, 8192, 1024, 1));
          wg_rs48(d2, fr[4 * ks], fr[4 * ks + 1], fr[4 * ks + 2], fr[4 * ks + 3], dsc(st + 2560 + ks * 32, 2048, 256, 3));
        }
        wg_commit();
      };
      load_a(f[0], 0);
#pragma unroll 1
      for (int c = 0; c < 10; c += 2) {
        issue(f[0], c);
        wg_wait<1>();
        if (c > 0 && lane == 0) mbar_arrive(bar(B_EMPTY + ((c - 1) & 3)));
        load_a(f[1], c + 1);
        issue(f[1], c + 1);
        wg_wait<1>();
        if (lane == 0) mbar_arrive(bar(B_EMPTY + (c & 3)));
        if (c < 8) load_a(f[0], c + 2);
      }
      mbar_wait(bar(B_PRM1), 0);
      mbar_wait(bar(B_EMPTY + 2), 1);
      wg_wait<0>();
      reg_fence(d1); reg_fence(d2);
      if (lane == 0) mbar_arrive(bar(B_GEMM));
      STAMP(2 + wg);
      const float2 st0 = lds64f(sm + T_ST + (warp * 16 + gq) * 8), st1 = lds64f(sm + T_ST + (warp * 16 + gq + 8) * 8);
      auto fin = [&](int seg, int t, float rs0, float rs1, float (&v)[4]) {
        const float* a = t < 8 ? &d1[(seg * 8 + t) * 4] : &d2[(seg * 2 + t - 8) * 4];
        const float4 ub = lds128f(sm + T_UB + ((seg * 10 + t) * 4 + q4) * 16);
        v[0] = fmaf(a[0], rs0, fmaf(st0.y, ub.x, ub.z)); v[1] = fmaf(a[1], rs0, fmaf(st0.y, ub.y, ub.w));
        v[2] = fmaf(a[2], rs1, fmaf(st1.y, ub.x, ub.z)); v[3] = fmaf(a[3], rs1, fmaf(st1.y, ub.y, ub.w));
      };
      uint32_t kp[10][2];
      const uint32_t kvw = sm + KVO + warp * (2 * GB) + ((lane >> 3) & 1) * GB + (lane >> 4) * 128 + (lane & 7) * 16;
#pragma unroll
      for (int pr = 0; pr < 2; pr++) {
        uint32_t mt[12][2];
#pragma unroll
        for (int t = 0; t < 5; t++) { float v[4]; fin(1, pr * 5 + t, st0.x, st1.x, v); kp[pr * 5 + t][0] = mt[t][0] = packbf(v[0], v[1]); kp[pr * 5 + t][1] = mt[t][1] = packbf(v[2], v[3]); }
#pragma unroll
        for (int t = 0; t < 5; t++) {
          float v[4]; fin(2, pr * 5 + t, st0.x, st1.x, v);
          const uint32_t a = packbf(v[0], v[1]), b = packbf(v[2], v[3]);
          if (t < 2) { mt[5 + t][0] = a; mt[5 + t][1] = b; }
          else if (t > 2) { mt[6 + t][0] = a; mt[6 + t][1] = b; }
          else {
            const uint32_t c0 = q4 == 2 ? 0x3f803f80u : 0x00003f80u, c1 = q4 == 0 ? 0x00003f80u : 0u;
            mt[7][0] = q4 < 2 ? a : c0; mt[7][1] = q4 < 2 ? b : c0; mt[8][0] = q4 < 2 ? c1 : a; mt[8][1] = q4 < 2 ? c1 : b;
          }
        }
#pragma unroll
        for (int t = 0; t < 10; t += 2) stsm4(kvw + pr * 1408 + t * 128, mt[t][0], mt[t][1], mt[t + 1][0], mt[t + 1][1]);
        asm volatile("stmatrix.sync.aligned.m8n8.x2.shared.b16 [%0], {%1,%2};" ::"r"(kvw - (lane >> 4) * 128 + pr * 1408 + 1280), "r"(mt[10][0]), "r"(mt[10][1]) : "memory");
      }
      fence_async_smem();
      bar_sync(2 + wg, 128);
      if ((tid & 127) == 0) {
        mbar_arrive(bar(B_KV + 4 + wg));
        if (m < 15) {
          bulk_store_wait(g_kv + (size_t)(cta * 2 + wg) * CHB, sm + KVO + wg * CHB, CHB);
          fence_async();
          flag_set(&g_kvflag[(cta * 2 + wg) * 8], tag);
        }
      }
      __syncwarp();
      const float qs = 0.22360679774997896f * 1.4426950408889634f;
#pragma unroll
      for (int pr = 0; pr < 2; pr++) {
        uint32_t qp[5][2]; float e0 = 0.f, e1 = 0.f, o0 = 0.f, o1 = 0.f;
#pragma unroll
        for (int t = 0; t < 5; t++) {
          float v[4]; fin(0, pr * 5 + t, st0.x * qs, st1.x * qs, v);
          qp[t][0] = packbf(v[0], v[1]); qp[t][1] = packbf(v[2], v[3]);
          const float s0 = fmaf(v[0], bflo(kp[pr * 5 + t][0]), v[1] * bfhi(kp[pr * 5 + t][0])), s1 = fmaf(v[2], bflo(kp[pr * 5 + t][1]), v[3] * bfhi(kp[pr * 5 + t][1]));
          if (t < 2) { e0 += s0; e1 += s1; } else if (t > 2) { o0 += s0; o1 += s1; }
          else { if (q4 < 2) { e0 += s0; e1 += s1; } else { o0 += s0; o1 += s1; } }
        }
        e0 += __shfl_xor_sync(~0u, e0, 1); e1 += __shfl_xor_sync(~0u, e1, 1); o0 += __shfl_xor_sync(~0u, o0, 1); o1 += __shfl_xor_sync(~0u, o1, 1);
        e0 += __shfl_xor_sync(~0u, e0, 2); e1 += __shfl_xor_sync(~0u, e1, 2); o0 += __shfl_xor_sync(~0u, o0, 2); o1 += __shfl_xor_sync(~0u, o1, 2);
        uint32_t (&qe)[8] = q[2 * pr]; uint32_t (&qo)[8] = q[2 * pr + 1];
        qe[0] = qp[0][0]; qe[1] = qp[0][1]; qe[2] = qp[1][0]; qe[3] = qp[1][1];
        qo[0] = qp[3][0]; qo[1] = qp[3][1]; qo[2] = qp[4][0]; qo[3] = qp[4][1];
        qe[4] = q4 < 2 ? qp[2][0] : 0u; qe[5] = q4 < 2 ? qp[2][1] : 0u; qo[4] = q4 < 2 ? 0u : qp[2][0]; qo[5] = q4 < 2 ? 0u : qp[2][1];
        qe[6] = q4 == 2 ? packbf(-e0, 0.f) : 0u; qe[7] = q4 == 2 ? packbf(-e1, 0.f) : 0u;
        qo[6] = q4 == 2 ? packbf(-o0, 0.f) : 0u; qo[7] = q4 == 2 ? packbf(-o1, 0.f) : 0u;
      }
      __syncwarp();
      if (lane == 0) mbar_arrive(bar(B_EPI1));
      STAMP(4 + wg);
    }
    const uint32_t ost = sm + (wg ? OST1 : 0u);
    {
      auto chunk = [&](int j) { return (sm + (j < 4 ? j * CHB : KVO + (j - 4) * CHB)) >> 4; };
      const int dd = 16 * wl + gq - 2 * q4;
      float o[4][12], s[2][32]; uint32_t p[2][16];
      float inv[4][2];
#pragma unroll 1
      for (int attempt = 0;; attempt++) {
#pragma unroll
        for (int h = 0; h < 4; h++)
#pragma unroll
          for (int j = 0; j < 12; j++) o[h][j] = 0.f;
#pragma unroll 1
        for (int it = 0; it < 4; it++) {
          if (it == 1) {
            const uint32_t ca = chunk(wg + 4), cb = chunk(wg);
            mbar_wait(bar(B_KV + wg), 0);
#pragma unroll
            for (int h = 0; h < 4; h++) {
              wg_fence(); issue_qk(s[0], q[h], ca, h); issue_qk(s[1], q[h], cb, h); wg_commit();
              wg_wait<0>(); reg_fence(s[0]); reg_fence(s[1]);
#pragma unroll
              for (int r = 0; r < 16; r++) {
                const int k8 = 8 * (2 * (r >> 2) + ((r >> 1) & 1) - (r & 1));
                const bool c0 = k8 <= dd, c1 = k8 + 1 <= dd;
                const uint32_t e = packbf(ex2(c0 ? s[0][2 * r] : s[1][2 * r]), ex2(c1 ? s[0][2 * r + 1] : s[1][2 * r + 1]));
                const uint32_t mk = (c0 ? 0xffffu : 0u) | (c1 ? 0xffff0000u : 0u);
                p[0][r] = e & mk; p[1][r] = e & ~mk;
              }
              wg_fence();
#pragma unroll
              for (int b = 0; b < 4; b++) { issue_pv1(o[h], p[0], ca, h, b); issue_pv1(o[h], p[1], cb, h, b); }
              wg_commit();
            }
          } else {
            const int j = wg + (it == 0 ? 3 : 4 - it);
            const uint32_t cb = chunk(j);
            mbar_wait(bar(B_KV + j), 0);
            wg_fence(); issue_qk(s[0], q[0], cb, 0); wg_commit();
#pragma unroll
            for (int h = 0; h < 4; h++) {
              if (h < 3) { wg_fence(); issue_qk(s[(h + 1) & 1], q[h + 1], cb, h + 1); wg_commit(); if (h == 0) wg_wait<1>(); else wg_wait<2>(); } else wg_wait<1>();
              reg_fence(s[h & 1]);
#pragma unroll
              for (int r = 0; r < 16; r++) {
                p[h & 1][r] = packbf(ex2(s[h & 1][2 * r]), ex2(s[h & 1][2 * r + 1]));
                if ((r & 3) == 3) { wg_fence(); issue_pv1(o[h], p[h & 1], cb, h, r >> 2); }
              }
              wg_commit();
            }
          }
        }
        wg_wait<0>();
        bool bad = false;
#pragma unroll
        for (int h = 0; h < 4; h++) {
          reg_fence(o[h]);
          const int src = (lane & ~3) | ((h & 1) ? 0 : 2);
          const float l0 = __shfl_sync(~0u, (h & 1) ? o[h][0] : o[h][8], src), l1 = __shfl_sync(~0u, (h & 1) ? o[h][2] : o[h][10], src);
          bad |= !(l0 > 1e-18f && l0 < 1e18f) || !(l1 > 1e-18f && l1 < 1e18f);
          inv[h][0] = __fdividef(1.f, l0); inv[h][1] = __fdividef(1.f, l1);
        }
        bad = bar_or(2 + wg, 128, bad);
        if (!bad || attempt) break;
#pragma unroll
        for (int h = 0; h < 4; h++) {
          q[h][6] = 0u; q[h][7] = 0u;
          float x0 = -3e38f, x1 = -3e38f;
#pragma unroll 1
          for (int j = 0; j < 5; j++) {
            if (m * 2 + wg + j < 4) continue;
            wg_fence(); issue_qk(s[0], q[h], chunk(wg + j), h); wg_commit(); wg_wait<0>(); reg_fence(s[0]);
#pragma unroll
            for (int e = 0; e < 32; e++) {
              const int r = e >> 1, k8 = 8 * (2 * (r >> 2) + ((r >> 1) & 1) - (r & 1)) + (e & 1);
              const bool lo = k8 <= dd, ok = j == 4 ? lo : (j == 0 ? !lo : true);
              const float v = ok ? s[0][e] : -3e38f;
              if (r & 1) x1 = fmaxf(x1, v); else x0 = fmaxf(x0, v);
            }
          }
          x0 = fmaxf(x0, __shfl_xor_sync(~0u, x0, 1)); x1 = fmaxf(x1, __shfl_xor_sync(~0u, x1, 1));
          x0 = fmaxf(x0, __shfl_xor_sync(~0u, x0, 2)); x1 = fmaxf(x1, __shfl_xor_sync(~0u, x1, 2));
          const float a0 = bfround(-x0), b0 = bfround(-x0 - a0), c0 = -x0 - a0 - b0, a1 = bfround(-x1), b1 = bfround(-x1 - a1), c1 = -x1 - a1 - b1;
          q[h][6] = q4 == 2 ? packbf(a0, b0) : (q4 == 3 ? packbf(c0, 0.f) : 0u);
          q[h][7] = q4 == 2 ? packbf(a1, b1) : (q4 == 3 ? packbf(c1, 0.f) : 0u);
        }
      }
      if ((tid & 127) == 0) mbar_arrive(bar(B_ATT));
      uint32_t ot[10][2];
#pragma unroll
      for (int pr = 0; pr < 2; pr++) {
        const float (&oe)[12] = o[2 * pr]; const float (&oo)[12] = o[2 * pr + 1];
        const float e0 = inv[2 * pr][0], e1 = inv[2 * pr][1], f0 = inv[2 * pr + 1][0], f1 = inv[2 * pr + 1][1];
        ot[5 * pr][0] = packbf(oe[0] * e0, oe[1] * e0); ot[5 * pr][1] = packbf(oe[2] * e1, oe[3] * e1);
        ot[5 * pr + 1][0] = packbf(oe[4] * e0, oe[5] * e0); ot[5 * pr + 1][1] = packbf(oe[6] * e1, oe[7] * e1);
        ot[5 * pr + 2][0] = q4 < 2 ? packbf(oe[8] * e0, oe[9] * e0) : packbf(oo[0] * f0, oo[1] * f0);
        ot[5 * pr + 2][1] = q4 < 2 ? packbf(oe[10] * e1, oe[11] * e1) : packbf(oo[2] * f1, oo[3] * f1);
        ot[5 * pr + 3][0] = packbf(oo[4] * f0, oo[5] * f0); ot[5 * pr + 3][1] = packbf(oo[6] * f1, oo[7] * f1);
        ot[5 * pr + 4][0] = packbf(oo[8] * f0, oo[9] * f0); ot[5 * pr + 4][1] = packbf(oo[10] * f1, oo[11] * f1);
      }
      const uint32_t ow = ost + (wl * 2 + ((lane >> 3) & 1)) * 1280 + (lane >> 4) * 128 + (lane & 7) * 16;
#pragma unroll
      for (int t = 0; t < 10; t += 2) stsm4(ow + t * 128, ot[t][0], ot[t][1], ot[t + 1][0], ot[t + 1][1]);
      fence_async_smem();
      bar_sync(2 + wg, 128);
      STAMP(6 + wg);
      if ((tid & 127) == 0) {
        bulk_store_wait(g_o + (size_t)(cta * 2 + wg) * 10240, ost, 10240);
        fence_async();
        flag_set(&g_oflag[(cta * 2 + wg) * 8], tag);
        mbar_arrive(bar(B_DONE0));
      }
      __syncwarp();
    }
    const int row0 = m * 128 + warp * 16 + gq;
    uint32_t x2p[10][2];
    float rstd0, rstd1, mean0, mean1; uint32_t key0, key1;
    {
#pragma unroll
      for (int t = 0; t < 10; t++) {
        x2p[t][0] = __ldg((const uint32_t*)(P.x + (size_t)row0 * 640 + g * 80 + t * 8 + q4 * 2));
        x2p[t][1] = __ldg((const uint32_t*)(P.x + (size_t)(row0 + 8) * 640 + g * 80 + t * 8 + q4 * 2));
      }
      float acc[40];
#pragma unroll
      for (int i = 0; i < 40; i++) acc[i] = 0.f;
#pragma unroll 1
      for (int j = 0; j < 8; j++) {
        const int js = j < 6 ? j : j - 6;
        const uint32_t a = (js == 0 ? ost : sm + 10240 * (2 * js - 1 + wg)) >> 4;
        const uint32_t b = (sm + (j < 7 ? WO + j * 12800 : WO7)) >> 4;
        mbar_wait(bar(B_WO + j), 0);
        if (j) mbar_wait(bar(B_OF + (j - 1) * 2 + wg), 0);
        wg_fence();
#pragma unroll
        for (int ks = 0; ks < 5; ks++) wg_ss80(acc, dsc(a + ks * 16, 128, 1280, 0), dsc(b + ks * 32, 2560, 256, 3));
        wg_commit();
        wg_wait<1>();
        if (lane == 0) { if (j == 1) mbar_arrive(bar(B_DONE0)); else if (j == 2) mbar_arrive(bar(B_DONE1)); else if (j == 6) mbar_arrive(bar(B_DONE5)); }
      }
      mbar_wait(bar(B_PRM2), 0);
      wg_wait<0>();
      reg_fence(acc);
      STAMP(8 + wg);
      float s10 = 0.f, s20 = 0.f, s30 = 0.f, s11 = 0.f, s21 = 0.f, s31 = 0.f;
#pragma unroll
      for (int t = 0; t < 10; t++) {
        const float4 ea = lds128f(sm + T_EA + (t * 4 + q4) * 16);
        const uint32_t u0 = packbf(fmaf(ea.x, acc[4 * t], bflo(x2p[t][0])), fmaf(ea.y, acc[4 * t + 1], bfhi(x2p[t][0])));
        const uint32_t u1 = packbf(fmaf(ea.x, acc[4 * t + 2], bflo(x2p[t][1])), fmaf(ea.y, acc[4 * t + 3], bfhi(x2p[t][1])));
        x2p[t][0] = u0; x2p[t][1] = u1;
        const float a = bflo(u0), b = bfhi(u0), c = bflo(u1), d = bfhi(u1);
        s10 += a + b; s20 = fmaf(a, a, fmaf(b, b, s20)); s30 = fmaf(a, ea.z, fmaf(b, ea.w, s30));
        s11 += c + d; s21 = fmaf(c, c, fmaf(d, d, s21)); s31 = fmaf(c, ea.z, fmaf(d, ea.w, s31));
      }
      {
        const bool od = q4 & 1;
        float a = (od ? s11 : s10) + __shfl_xor_sync(~0u, od ? s10 : s11, 1), b = (od ? s21 : s20) + __shfl_xor_sync(~0u, od ? s20 : s21, 1), c = (od ? s31 : s30) + __shfl_xor_sync(~0u, od ? s30 : s31, 1);
        a += __shfl_xor_sync(~0u, a, 2); b += __shfl_xor_sync(~0u, b, 2); c += __shfl_xor_sync(~0u, c, 2);
        if (q4 < 2) ll_st128(&g_part[cta * 128 + warp * 16 + gq * 2 + q4], __float_as_uint(a), __float_as_uint(b), __float_as_uint(c), tag);
      }
      float t1[2], t2[2], t3[2];
      {
        const uint4* pp = &g_part[(m * 8 + q4 * 2) * 128 + warp * 16 + gq * 2];
        uint4 w[4]; int it = 0;
        do {
          w[0] = ll_ld128(pp); w[1] = ll_ld128(pp + 1); w[2] = ll_ld128(pp + 128); w[3] = ll_ld128(pp + 129);
          if (++it > SPIN_LIMIT) __trap();
        } while (w[0].w != tag || w[1].w != tag || w[2].w != tag || w[3].w != tag);
#pragma unroll
        for (int r = 0; r < 2; r++) {
          t1[r] = __uint_as_float(w[r].x) + __uint_as_float(w[2 + r].x); t2[r] = __uint_as_float(w[r].y) + __uint_as_float(w[2 + r].y); t3[r] = __uint_as_float(w[r].z) + __uint_as_float(w[2 + r].z);
        }
        __syncwarp();
#pragma unroll
        for (int o = 1; o <= 2; o <<= 1)
#pragma unroll
          for (int r = 0; r < 2; r++) { t1[r] += __shfl_xor_sync(~0u, t1[r], o); t2[r] += __shfl_xor_sync(~0u, t2[r], o); t3[r] += __shfl_xor_sync(~0u, t3[r], o); }
      }
      const float2 sc = lds64f(sm + T_SC);
      mean0 = t1[0] * (1.f / 640.f); mean1 = t1[1] * (1.f / 640.f);
      rstd0 = rsqrtf(fmaxf(fmaf(-mean0, mean0, t2[0] * (1.f / 640.f)), 0.f) + 1e-5f); rstd1 = rsqrtf(fmaxf(fmaf(-mean1, mean1, t2[1] * (1.f / 640.f)), 0.f) + 1e-5f);
      const float r0 = fmaf(rstd0, fmaf(-mean0, sc.x, t3[0]), sc.y), r1 = fmaf(rstd1, fmaf(-mean1, sc.x, t3[1]), sc.y);
      key0 = (sortable(r0) & ~2047u) | (2047 - row0); key1 = (sortable(r1) & ~2047u) | (2047 - row0 - 8);
    }
    STAMP(10 + wg);
    uint32_t c1k, c2k;
    top2(key0, key1, c1k, c2k);
    if (lane == 0) sts64(sm + T_KEY + warp * 8, c1k, c2k);
    bar_sync(1, 256);
    top2(lds32(sm + T_KEY + (lane & 15) * 4), 0u, c1k, c2k);
    if (tid < 2) ll_st128(&g_keys[(g * 16 + m) * 2 + tid], c1k, c2k, 0u, tag);
    {
      uint32_t h2p[10][2], op[10][2];
#pragma unroll
      for (int t = 0; t < 10; t++) {
        const float4 eb = lds128f(sm + T_EB + (t * 4 + q4) * 16);
        h2p[t][0] = packbf(fmaf((bflo(x2p[t][0]) - mean0) * rstd0, eb.x, eb.z), fmaf((bfhi(x2p[t][0]) - mean0) * rstd0, eb.y, eb.w));
        h2p[t][1] = packbf(fmaf((bflo(x2p[t][1]) - mean1) * rstd1, eb.x, eb.z), fmaf((bfhi(x2p[t][1]) - mean1) * rstd1, eb.y, eb.w));
      }
#pragma unroll
      for (int r = 0; r < 2; r++) {
        const uint32_t k = r ? key1 : key0;
        if (k == c1k || k == c2k) {
          const int base = ((m * 2 + (k == c2k)) * 8 + g) * 20 + q4;
#pragma unroll
          for (int s = 0; s < 5; s++) ll_st128(&g_h2[base + s * 4], h2p[2 * s][r], h2p[2 * s + 1][r], 0u, tag);
#pragma unroll
          for (int s = 0; s < 5; s++) ll_st128(&g_x2[base + s * 4], x2p[2 * s][r], x2p[2 * s + 1][r], 0u, tag);
        }
      }
      __syncwarp();
#pragma unroll
      for (int t = 0; t < 10; t++) {
        const float2 gb = lds64f(sm + T_EC + (t * 4 + q4) * 8);
        op[t][0] = packbf(fmaf(gb.x, bflo(h2p[t][0]), bflo(x2p[t][0])), fmaf(gb.y, bfhi(h2p[t][0]), bfhi(x2p[t][0])));
        op[t][1] = packbf(fmaf(gb.x, bflo(h2p[t][1]), bflo(x2p[t][1])), fmaf(gb.y, bfhi(h2p[t][1]), bfhi(x2p[t][1])));
      }
      const uint32_t ow = sm + T_OUT + (warp * 16 + (lane & 15)) * 176 + (lane >> 4) * 16;
#pragma unroll
      for (int t = 0; t < 10; t += 2) stsm4(ow + t * 16, op[t][0], op[t][1], op[t + 1][0], op[t + 1][1]);
      __syncwarp();
    }
    const int cr1 = 2047 - (int)(c1k & 2047u), cr2 = 2047 - (int)(c2k & 2047u);
#pragma unroll
    for (int i = 0; i < 5; i++) {
      const int e = i * 32 + lane, r = e / 10, ch = e - r * 10, row = m * 128 + warp * 16 + r;
      const uint4 v = lds128(sm + T_OUT + (warp * 16 + r) * 176 + ch * 16);
      if (row != cr1 && row != cr2) *(uint4*)(P.out + (size_t)row * 640 + g * 80 + ch * 8) = v;
    }
    STAMP(12 + wg);
    uint32_t k1, k2;
    {
      uint4 w = make_uint4(0u, 0u, 0u, 0u);
      if (lane < 16) w = ll_wait128(&g_keys[(g * 16 + lane) * 2], tag);
      __syncwarp();
      top2(w.x, w.y, k1, k2);
      const uint32_t b1 = __ballot_sync(~0u, w.y == k1), b2 = __ballot_sync(~0u, w.y == k2);
      const int tok = (lane >> 2) & 1, kk = lane >> 3;
      const int srow = 2047 - (int)((tok ? k2 : k1) & 2047u);
      const int slot = (srow >> 7) * 2 + ((tok ? b2 : b1) ? 1 : 0);
      STAMP(14 + wg);
      if (cta < 96) {
        const uint4* hp = &g_h2[(slot * 8 + warp) * 20 + q4];
        uint4 a0, a1; int it = 0;
        do { a0 = ll_ld128(hp + kk * 4); a1 = ll_ld128(hp + 16); if (++it > SPIN_LIMIT) __trap(); } while (a0.w != tag || a1.w != tag);
        __syncwarp();
        mbar_wait(bar(B_MOEW), 0);
        float d[4][4];
#pragma unroll
        for (int n = 0; n < 4; n++) { d[n][0] = 0.f; d[n][1] = 0.f; d[n][2] = 0.f; d[n][3] = 0.f; }
        const uint32_t wb = sm + MOEW + (warp * 80 + (lane & 15)) * 80 + (lane >> 4) * 16;
#pragma unroll
        for (int s = 0; s < 5; s++) {
          const bool on = s < 4 ? kk == s : kk == 0;
          const uint32_t x = on ? (s < 4 ? a0.x : a1.x) : 0u, y = on ? (s < 4 ? a0.y : a1.y) : 0u;
          uint32_t bg[4], bu[4];
          ldsm4t(bg, wb + s * 1280); ldsm4t(bu, wb + s * 1280 + 32);
          mma16(d[0], x, y, bg[0], bg[1]); mma16(d[1], x, y, bg[2], bg[3]); mma16(d[2], x, y, bu[0], bu[1]); mma16(d[3], x, y, bu[2], bu[3]);
        }
#pragma unroll
        for (int n = 0; n < 4; n++) {
          d[n][0] += __shfl_xor_sync(~0u, d[n][0], 8); d[n][1] += __shfl_xor_sync(~0u, d[n][1], 8);
          d[n][0] += __shfl_xor_sync(~0u, d[n][0], 16); d[n][1] += __shfl_xor_sync(~0u, d[n][1], 16);
        }
        {
          const float v0 = kk == 0 ? d[0][0] : kk == 1 ? d[1][0] : kk == 2 ? d[2][0] : d[3][0], v1 = kk == 0 ? d[0][1] : kk == 1 ? d[1][1] : kk == 2 ? d[2][1] : d[3][1];
          sts64(sm + T_MRED + warp * 256 + lane * 8, __float_as_uint(v0), __float_as_uint(v1));
        }
        bar_sync(1, 256);
        if (warp == 0) {
          float v0 = 0.f, v1 = 0.f;
#pragma unroll
          for (int w2 = 0; w2 < 8; w2++) { const float2 t = lds64f(sm + T_MRED + w2 * 256 + lane * 8); v0 += t.x; v1 += t.y; }
          v0 = bfround(v0); v1 = bfround(v1);
          const float u0 = __shfl_down_sync(~0u, v0, 16), u1 = __shfl_down_sync(~0u, v1, 16);
          const uint32_t gu = packbf(bfround(silu_f(v0)) * u0, bfround(silu_f(v1)) * u1);
          const uint32_t gu2 = __shfl_down_sync(~0u, gu, 8);
          if (lane < 8) ll_st128(&g_gu[cta * 8 + lane], gu, gu2, 0u, tag);
        }
      } else {
        const int j = cta - 96;
        uint32_t fh = 0, fx = 0, fg = 0;
        if (tid < 20) {
          const int tk = tid / 10, pi = (j & 3) * 10 + (tid - tk * 10), t = pi >> 2;
          const int sr = 2047 - (int)((tk ? k2 : k1) & 2047u), sl = (sr >> 7) * 2 + ((tk ? b2 : b1) ? 1 : 0);
          const int ix = (sl * 8 + (j >> 2)) * 20 + (t >> 1) * 4 + (pi & 3);
          const uint4 wh = ll_wait128(&g_h2[ix], tag), wx = ll_wait128(&g_x2[ix], tag);
          fh = (t & 1) ? wh.y : wh.x; fx = (t & 1) ? wx.y : wx.x;
          fg = ll_wait64(&g_mod[1600 + j * 10 + (tid - tk * 10)], tag);
        }
        __syncwarp();
        mbar_wait(bar(B_MOEW), 0);
        const uint4* gp = &g_gu[(warp * 12 + kk) * 8 + (lane & 7)];
        uint4 a[3]; int it = 0;
        do { a[0] = ll_ld128(gp); a[1] = ll_ld128(gp + 32); a[2] = ll_ld128(gp + 64); if (++it > SPIN_LIMIT) __trap(); } while (a[0].w != tag || a[1].w != tag || a[2].w != tag);
        __syncwarp();
        float d[3][4];
#pragma unroll
        for (int n = 0; n < 3; n++) { d[n][0] = 0.f; d[n][1] = 0.f; d[n][2] = 0.f; d[n][3] = 0.f; }
        const uint32_t wb = sm + MOEW + (warp * 192 + (lane & 15)) * 48;
#pragma unroll
        for (int s = 0; s < 12; s++) {
          const bool on = kk == (s & 3);
          const uint32_t x = on ? a[s >> 2].x : 0u, y = on ? a[s >> 2].y : 0u;
          uint32_t b4[4], b2r[2];
          ldsm4t(b4, wb + s * 768 + (lane >> 4) * 16); ldsm2t(b2r, wb + s * 768 + 32);
          mma16(d[0], x, y, b4[0], b4[1]); mma16(d[1], x, y, b4[2], b4[3]); mma16(d[2], x, y, b2r[0], b2r[1]);
        }
#pragma unroll
        for (int n = 0; n < 3; n++) {
          d[n][0] += __shfl_xor_sync(~0u, d[n][0], 8); d[n][1] += __shfl_xor_sync(~0u, d[n][1], 8);
          d[n][0] += __shfl_xor_sync(~0u, d[n][0], 16); d[n][1] += __shfl_xor_sync(~0u, d[n][1], 16);
        }
        {
          const float v0 = kk == 0 ? d[0][0] : kk == 1 ? d[1][0] : d[2][0], v1 = kk == 0 ? d[0][1] : kk == 1 ? d[1][1] : d[2][1];
          sts64(sm + T_MRED + warp * 256 + lane * 8, __float_as_uint(v0), __float_as_uint(v1));
        }
        bar_sync(1, 256);
        if (tid < 20) {
          const int tk = tid / 10, pl = tid - tk * 10;
          float v0 = 0.f, v1 = 0.f;
#pragma unroll
          for (int w2 = 0; w2 < 8; w2++) { const float2 t = lds64f(sm + T_MRED + w2 * 256 + ((pl >> 2) * 8 + tk * 4 + (pl & 3)) * 8); v0 += t.x; v1 += t.y; }
          const uint32_t kx = tk ? k2 : k1;
          const float sg = bfround(1.f / (1.f + __expf(-bfround(unsortable((kx & ~2047u) | 1024u)))));
          const float y0 = bfround(bfround(v0) * sg), y1 = bfround(bfround(v1) * sg);
          *(uint32_t*)(P.out + (size_t)(2047 - (int)(kx & 2047u)) * 640 + j * 20 + pl * 2) =
              packbf(fmaf(bflo(fg), bfround(bflo(fh) + y0), bflo(fx)), fmaf(bfhi(fg), bfround(bfhi(fh) + y1), bfhi(fx)));
        }
      }
    }
    if (lane < 20) {
      const uint32_t ck = lane < 10 ? c1k : c2k;
      const int row = lane < 10 ? cr1 : cr2, ch = lane < 10 ? lane : lane - 10;
      if (((row >> 4) & 7) == warp && ck != k1 && ck != k2)
        *(uint4*)(P.out + (size_t)row * 640 + g * 80 + ch * 8) = lds128(sm + T_OUT + (row & 127) * 176 + ch * 16);
    }
    if (cta == 0 && tid == 0) asm volatile("st.relaxed.gpu.global.u32 [%0], %1;" ::"l"(&g_epoch), "r"(tag) : "memory");
    STAMP(16 + wg);
  } else {
    asm volatile("setmaxnreg.dec.sync.aligned.u32 40;");
  if (tid == 256) {
    if (sm & 1023) __trap();
    for (int i = 0; i < 4; i++) { mbar_init(bar(B_FULL + i), 1); mbar_init(bar(B_EMPTY + i), 8); }
    asm volatile("fence.mbarrier_init.release.cluster;" ::: "memory");
    fence_async_smem();
    for (int c = 0; c < 4; c++) {
      const uint32_t st = sm + c * STAGE;
      mbar_expect_tx(bar(B_FULL + c), STAGE);
      tma2d(st, &P.mx, c * 64, m * 128, bar(B_FULL + c));
      tma3d(st + 16384, &P.mw64, g * 80, c * 64, 0, bar(B_FULL + c));
      tma3d(st + 40960, &P.mw16, g * 80 + 64, c * 64, 0, bar(B_FULL + c));
    }
    for (int i = 0; i < 6; i++) mbar_init(bar(B_KV + i), 1);
    mbar_init(bar(B_PRM1), 3); mbar_init(bar(B_EPI1), 8);
    for (int i = 0; i < 22; i++) mbar_init(bar(B_WO + i), 1);
    mbar_init(bar(B_DONE0), 10); mbar_init(bar(B_DONE1), 8); mbar_init(bar(B_DONE5), 8);
    mbar_init(bar(B_ATT), 2); mbar_init(bar(B_PRM2), 3); mbar_init(bar(B_MOEW), 96); mbar_init(bar(B_GEMM), 8);
    asm volatile("fence.mbarrier_init.release.cluster;" ::: "memory");
    fence_async_smem();
  }

    __syncwarp();
    tag += 1;
    bar_sync(0, 384);
    if (warp == 8) {
      if (lane == 0) {
        for (int c = 4; c < 10; c++) {
          const int s = c & 3; const uint32_t st = sm + s * STAGE;
          mbar_wait(bar(B_EMPTY + s), ((c >> 2) & 1) ^ 1);
          mbar_expect_tx(bar(B_FULL + s), STAGE);
          tma2d(st, &P.mx, c * 64, m * 128, bar(B_FULL + s));
          tma3d(st + 16384, &P.mw64, g * 80, c * 64, 0, bar(B_FULL + s));
          tma3d(st + 40960, &P.mw16, g * 80 + 64, c * 64, 0, bar(B_FULL + s));
        }
      }
      __syncwarp();
      mbar_wait(bar(B_GEMM), 0);
      {
        const int j = lane == 0 ? 3 : lane == 1 ? 1 : lane == 2 ? 0 : 2;
        const int src = (cta - 16 + (j >> 1) * 8) * 2 + (j & 1);
        bool pend = lane < 4 && m * 2 + j >= 4;
        int it = 0;
        while (__any_sync(~0u, pend)) {
          if (pend && flag_get(&g_kvflag[src * 8]) == tag) {
            fence_async();
            mbar_expect_tx(bar(B_KV + j), CHB);
            bulk_load(sm + j * CHB, g_kv + (size_t)src * CHB, CHB, bar(B_KV + j));
            pend = false;
          }
          if (++it > SPIN_LIMIT) __trap();
        }
      }
      mbar_wait(bar(B_EPI1), 0);
      if (lane < 7) {
        mbar_expect_tx(bar(B_WO + lane), 12800);
        tma3d(sm + WO + lane * 12800, &P.mwo, 0, ((g + lane) & 7) * 80, g * 5, bar(B_WO + lane));
      }
      __syncwarp();
      mbar_wait(bar(B_ATT), 0);
      if (lane == 0) {
        mbar_expect_tx(bar(B_WO + 7), 12800);
        tma3d(sm + WO7, &P.mwo, 0, ((g + 7) & 7) * 80, g * 5, bar(B_WO + 7));
      }
      {
        const int j = 1 + (lane >> 1), w = lane & 1, js = j < 6 ? j : j - 6;
        const int src = (m * 8 + ((g + j) & 7)) * 2 + w;
        const uint32_t dst = sm + (js == 0 ? (w ? OST1 : 0u) : 10240 * (2 * js - 1 + w));
        bool pend = lane < 14;
        int it = 0;
        while (__any_sync(~0u, pend)) {
          if (pend) {
            uint32_t ok = 1;
            if (j >= 6) asm volatile("{ .reg .pred p; mbarrier.test_wait.parity.shared::cta.b64 p, [%1], 0; selp.u32 %0,1,0,p; }" : "=r"(ok) : "r"(bar(j == 6 ? B_DONE0 : B_DONE1)) : "memory");
            if (ok && flag_get(&g_oflag[src * 8]) == tag) {
              fence_async();
              mbar_expect_tx(bar(B_OF + lane), 10240);
              bulk_load(dst, g_o + (size_t)src * 10240, 10240, bar(B_OF + lane));
              pend = false;
            }
          }
          if (++it > SPIN_LIMIT) __trap();
        }
      }
    } else {
      const int t = tid - 288, aw = warp - 9;
      const int hf = t & 1, r0 = t >> 1;
      for (int i = t; i < 640; i += 96) sts32f(sm + T_SIL + i * 4, bfround(silu_f(__bfloat162float(P.c[i]))));
      for (int i = t; i < 320; i += 96) {
        uint2 v = ll_wait64x2(&g_mod[2 * i], tag);
        if (i >= 160) { v.x = hadd2(v.x, 0x3f803f80u); v.y = hadd2(v.y, 0x3f803f80u); }
        sts64(sm + T_MOD + i * 8, v.x, v.y);
      }
      bar_sync(4, 96);
      if (cta < 120) {
        float u[8] = {0.f, 0.f, 0.f, 0.f, 0.f, 0.f, 0.f, 0.f}, b[8] = {0.f, 0.f, 0.f, 0.f, 0.f, 0.f, 0.f, 0.f};
#pragma unroll 1
        for (int bt = 0; bt < 14; bt += 4) {
          uint4 w[4];
#pragma unroll
          for (int i = 0; i < 4; i++) { const int r = r0 + 48 * (bt + i); w[i] = r < 640 ? ldg128(P.wqkv + (size_t)r * 1920 + cta * 16 + hf * 8) : make_uint4(0u, 0u, 0u, 0u); }
#pragma unroll
          for (int i = 0; i < 4; i++) {
            const int r = min(r0 + 48 * (bt + i), 639);
            const uint32_t sa = lds32(sm + T_MOD + (r >> 1) * 4), c1 = lds32(sm + T_MOD + 1280 + (r >> 1) * 4);
            fma8(u, w[i], (r & 1) ? bfhi(c1) : bflo(c1)); fma8(b, w[i], (r & 1) ? bfhi(sa) : bflo(sa));
          }
        }
        const float uu = red8(u, lane), bb = red8(b, lane);
        if (lane < 16) sts64(sm + T_RED2 + (aw * 16 + red8_col(lane)) * 8, __float_as_uint(uu), __float_as_uint(bb));
        bar_sync(4, 96);
        if (t < 16) {
          const float2 a0 = lds64f(sm + T_RED2 + t * 8), a1 = lds64f(sm + T_RED2 + 128 + t * 8), a2 = lds64f(sm + T_RED2 + 256 + t * 8);
          ll_st128(&g_ub[cta * 16 + t], __float_as_uint(a0.x + a1.x + a2.x), __float_as_uint(a0.y + a1.y + a2.y), 0u, tag);
        }
        bar_sync(4, 96);
      }
      if (cta < 112) {
        const int G = 128 + cta;
        float a[8] = {0.f, 0.f, 0.f, 0.f, 0.f, 0.f, 0.f, 0.f};
#pragma unroll 1
        for (int bt = 0; bt < 14; bt += 7) {
          uint4 w[7];
#pragma unroll
          for (int i = 0; i < 7; i++) { const int r = r0 + 48 * (bt + i); w[i] = r < 640 ? ldg128(P.wmod + (size_t)r * 3840 + G * 16 + hf * 8) : make_uint4(0u, 0u, 0u, 0u); }
#pragma unroll
          for (int i = 0; i < 7; i++) fma8(a, w[i], lds32f(sm + T_SIL + min(r0 + 48 * (bt + i), 639) * 4));
        }
        const float v = red8(a, lane);
        if (lane < 16) sts32f(sm + T_RED2 + (aw * 16 + red8_col(lane)) * 4, v);
        bar_sync(4, 96);
        if (t < 8) {
          const float2 a0 = lds64f(sm + T_RED2 + t * 8), a1 = lds64f(sm + T_RED2 + 64 + t * 8), a2 = lds64f(sm + T_RED2 + 128 + t * 8);
          ll_st64(&g_mod[G * 8 + t], packbf(a0.x + a1.x + a2.x, a0.y + a1.y + a2.y), tag);
        }
      }
      if (t == 32) {
        bulk_prefetch(P.wo + cta * 3200, 6400);
        bulk_prefetch(P.wg + cta * 7680, 15360); bulk_prefetch(P.wu + cta * 7680, 15360); bulk_prefetch(P.wd + cta * 7680, 15360);
      }
      for (int i = t; i < 128; i += 96) { const uint4 v = ll_wait128(&g_stat[m * 128 + i], tag); sts64(sm + T_ST + i * 8, v.x, v.y); }
      for (int i = t; i < 240; i += 96) {
        const int seg = i / 80, cc = i - seg * 80;
        const uint4 v = ll_wait128(&g_ub[seg * 640 + g * 80 + cc], tag);
        const float sc = seg == 0 ? 0.22360679774997896f * 1.4426950408889634f : 1.f;
        const uint32_t ad = sm + T_UB + (i >> 1) * 16 + (i & 1) * 4;
        sts32f(ad, __uint_as_float(v.x) * sc); sts32f(ad + 8, __uint_as_float(v.y) * sc);
      }
      __syncwarp();
      if (lane == 0) mbar_arrive(bar(B_PRM1));
      {
        float U = 0.f, Bc = 0.f;
        for (int i = t; i < 320; i += 96) {
          const uint32_t sb = ll_wait64(&g_mod[960 + i], tag), c2 = hadd2(ll_wait64(&g_mod[1280 + i], tag), 0x3f803f80u);
          const uint32_t wr = __ldg((const uint32_t*)P.wr + i);
          const float w0 = bflo(c2) * bflo(wr), w1 = bfhi(c2) * bfhi(wr);
          U += w0 + w1; Bc = fmaf(bflo(sb), bflo(wr), fmaf(bfhi(sb), bfhi(wr), Bc));
          const int li = i - g * 40;
          if (li >= 0 && li < 40) {
            const uint32_t ga = ll_wait64(&g_mod[640 + i], tag), gb = ll_wait64(&g_mod[1600 + i], tag);
            sts128(sm + T_EA + li * 16, make_uint4(ga << 16, ga & 0xffff0000u, __float_as_uint(w0), __float_as_uint(w1)));
            sts128(sm + T_EB + li * 16, make_uint4(c2 << 16, c2 & 0xffff0000u, sb << 16, sb & 0xffff0000u));
            sts64(sm + T_EC + li * 8, gb << 16, gb & 0xffff0000u);
          }
        }
        __syncwarp();
#pragma unroll
        for (int o = 16; o; o >>= 1) { U += __shfl_xor_sync(~0u, U, o); Bc += __shfl_xor_sync(~0u, Bc, o); }
        if (lane == 0) sts64(sm + T_SC + 8 + aw * 8, __float_as_uint(U), __float_as_uint(Bc));
        bar_sync(4, 96);
        if (t == 0) {
          const float2 a0 = lds64f(sm + T_SC + 8), a1 = lds64f(sm + T_SC + 16), a2 = lds64f(sm + T_SC + 24);
          sts64(sm + T_SC, __float_as_uint(a0.x + a1.x + a2.x), __float_as_uint(a0.y + a1.y + a2.y));
        }
        __syncwarp();
        if (lane == 0) mbar_arrive(bar(B_PRM2));
      }
      if (m < 2) {
        mbar_wait(bar(B_GEMM), 0);
        const int n = (4 - 2 * m) * (CHB / 16);
        for (int i = t; i < n; i += 96) sts128(sm + i * 16, make_uint4(0u, 0u, 0u, 0u));
        fence_async_smem();
        bar_sync(4, 96);
        if (t < 4 - 2 * m) mbar_arrive(bar(B_KV + t));
      }
      mbar_wait(bar(B_DONE5), 0);
      if (cta < 96) {
        for (int i = t; i < 2560; i += 96) { const int r = i >> 2, c = i & 3; cp16(sm + MOEW + r * 80 + c * 16, ((c & 2) ? P.wu : P.wg) + (size_t)r * 1536 + cta * 16 + (c & 1) * 8); }
      } else {
        for (int i = t; i < 7680; i += 96) { const int r = i / 5, c = i - r * 5; cp8(sm + MOEW + r * 48 + c * 8, P.wd + (size_t)r * 640 + (cta - 96) * 20 + c * 4); }
      }
      cp_arrive(bar(B_MOEW));
      asm volatile("cp.async.wait_all;" ::: "memory");
    }
  }
}

typedef CUresult (*EncFn)(CUtensorMap*, CUtensorMapDataType, cuuint32_t, void*, const cuuint64_t*, const cuuint64_t*, const cuuint32_t*, const cuuint32_t*, CUtensorMapInterleave, CUtensorMapSwizzle, CUtensorMapL2promotion, CUtensorMapFloatOOBfill);
static void make_map(EncFn enc, CUtensorMap* mp, const void* ptr, int rank, const cuuint64_t* dims, const cuuint64_t* strides, const cuuint32_t* box, CUtensorMapSwizzle sw) {
  const cuuint32_t es[3] = {1, 1, 1};
  enc(mp, CU_TENSOR_MAP_DATA_TYPE_BFLOAT16, rank, (void*)ptr, dims, strides, box, es, CU_TENSOR_MAP_INTERLEAVE_NONE, sw, CU_TENSOR_MAP_L2_PROMOTION_L2_128B, CU_TENSOR_MAP_FLOAT_OOB_FILL_NONE);
}
extern "C" void kernel_launch(void* const* d_in, const int* in_sizes, int n_in, void* d_out, int out_size) {
  void* fn = nullptr; cudaDriverEntryPointQueryResult qr;
  cudaGetDriverEntryPoint("cuTensorMapEncodeTiled", &fn, cudaEnableDefault, &qr);
  EncFn enc = (EncFn)fn;
  Params P;
  P.x = (const __nv_bfloat16*)d_in[0]; P.wqkv = (const __nv_bfloat16*)d_in[1]; P.wo = (const __nv_bfloat16*)d_in[2];
  P.wr = (const __nv_bfloat16*)d_in[4]; P.wg = (const __nv_bfloat16*)d_in[5]; P.wu = (const __nv_bfloat16*)d_in[6]; P.wd = (const __nv_bfloat16*)d_in[7];
  P.c = (const __nv_bfloat16*)d_in[8]; P.wmod = (const __nv_bfloat16*)d_in[9]; P.out = (__nv_bfloat16*)d_out;
  { const cuuint64_t d[2] = {640, 2048}, s[1] = {1280}; const cuuint32_t b[2] = {64, 128}; make_map(enc, &P.mx, P.x, 2, d, s, b, CU_TENSOR_MAP_SWIZZLE_128B); }
  { const cuuint64_t d[3] = {640, 640, 3}, s[2] = {3840, 1280}; const cuuint32_t b[3] = {64, 64, 3}; make_map(enc, &P.mw64, P.wqkv, 3, d, s, b, CU_TENSOR_MAP_SWIZZLE_128B); }
  { const cuuint64_t d[3] = {640, 640, 3}, s[2] = {3840, 1280}; const cuuint32_t b[3] = {16, 64, 3}; make_map(enc, &P.mw16, P.wqkv, 3, d, s, b, CU_TENSOR_MAP_SWIZZLE_32B); }
  { const cuuint64_t d[3] = {16, 640, 40}, s[2] = {1280, 32}; const cuuint32_t b[3] = {16, 80, 5}; make_map(enc, &P.mwo, P.wo, 3, d, s, b, CU_TENSOR_MAP_SWIZZLE_32B); }
  cudaFuncSetAttribute(fused_kernel, cudaFuncAttributeMaxDynamicSharedMemorySize, SMEM_BYTES);
  fused_kernel<<<128, 384, SMEM_BYTES>>>(P);
}
```

```cpp
#include <cuda_runtime.h>
#include <cuda.h>
#include <cuda_bf16.h>
#include <stdint.h>

typedef unsigned long long u64;
#define SPIN_LIMIT 1000000
#define MBAR_LIMIT 200000
#define TRAP() asm volatile("trap;")

__device__ __align__(128) unsigned g_epoch[8 * 32];
__device__ __align__(128) uint2 g_mod[1920];
__device__ __align__(128) uint2 g_modr[8 * 640];
__device__ __align__(128) uint4 g_rc[128 * 2];
__device__ __align__(128) uint2 g_stat[2048];
__device__ __align__(1024) uint4 g_xch[128 * 4096];
__device__ __align__(128) uint4 g_part[16 * 8 * 128];
__device__ __align__(128) uint4 g_keys[64 * 16 * 2];
__device__ __align__(128) uint4 g_h2[8 * 16 * 2 * 8 * 20];
__device__ __align__(128) uint4 g_x2[16 * 2 * 8 * 20];
__device__ __align__(128) uint4 g_gu[4 * 96 * 8];
#define STAMP(i)
#define g_prof_set(i)

__device__ __forceinline__ uint32_t smem_u32(const void* p) { return (uint32_t)__cvta_generic_to_shared(p); }
__device__ __forceinline__ void mbar_init(uint32_t bar, int cnt) { asm volatile("mbarrier.init.shared::cta.b64 [%0], %1;" ::"r"(bar), "r"(cnt) : "memory"); }
__device__ __forceinline__ void mbar_expect_tx(uint32_t bar, uint32_t bytes) { asm volatile("mbarrier.arrive.expect_tx.shared::cta.b64 _, [%0], %1;" ::"r"(bar), "r"(bytes) : "memory"); }
__device__ __forceinline__ void mbar_arrive(uint32_t bar) { asm volatile("mbarrier.arrive.shared::cta.b64 _, [%0];" ::"r"(bar) : "memory"); }
__device__ __forceinline__ void mbar_wait(uint32_t bar, uint32_t parity) {
  uint32_t ok; int it = 0;
  do {
    asm volatile("{ .reg .pred p; mbarrier.try_wait.parity.shared::cta.b64 p, [%1], %2; selp.u32 %0,1,0,p; }" : "=r"(ok) : "r"(bar), "r"(parity) : "memory");
    if (++it > MBAR_LIMIT) TRAP();
  } while (!ok);
}
__device__ __forceinline__ void bar_sync(int id, int n) { asm volatile("bar.sync %0, %1;" ::"r"(id), "r"(n) : "memory"); }
__device__ __forceinline__ bool bar_or(int id, int n, bool v) {
  uint32_t r;
  asm volatile("{ .reg .pred p, q; setp.ne.u32 p, %3, 0; barrier.cta.red.or.aligned.pred q, %1, %2, p; selp.u32 %0,1,0,q; }" : "=r"(r) : "r"(id), "r"(n), "r"((uint32_t)v) : "memory");
  return r != 0;
}
__device__ __forceinline__ void fence_async() { asm volatile("fence.proxy.async;" ::: "memory"); }
__device__ __forceinline__ void fence_async_smem() { asm volatile("fence.proxy.async.shared::cta;" ::: "memory"); }
__device__ __forceinline__ void bulk_load(uint32_t dst, const void* src, uint32_t bytes, uint32_t bar) { asm volatile("cp.async.bulk.shared::cluster.global.mbarrier::complete_tx::bytes [%0], [%1], %2, [%3];" ::"r"(dst), "l"(src), "r"(bytes), "r"(bar) : "memory"); }
__device__ __forceinline__ uint32_t opaque_u(uint32_t v) { asm volatile("" : "+r"(v)); return __shfl_sync(~0u, v, 0); }
__device__ __forceinline__ void stg32(void* p, uint32_t v) { asm volatile("st.global.u32 [%0], %1;" ::"l"(p), "r"(v) : "memory"); }
__device__ __forceinline__ void fence_gpu() { asm volatile("fence.acq_rel.gpu;" ::: "memory"); }
__device__ __forceinline__ uint2 lds64(uint32_t addr) { uint2 v; asm volatile("ld.shared.v2.u32 {%0,%1}, [%2];" : "=r"(v.x), "=r"(v.y) : "r"(addr) : "memory"); return v; }
__device__ __forceinline__ void spin_until(long long t) { while (clock64() < t); }
__device__ __forceinline__ void bulk_store_wait(void* dst, uint32_t src, uint32_t bytes) {
  asm volatile("cp.async.bulk.global.shared::cta.bulk_group [%0], [%1], %2;" ::"l"(dst), "r"(src), "r"(bytes) : "memory");
  asm volatile("cp.async.bulk.commit_group;" ::: "memory");
  asm volatile("cp.async.bulk.wait_group 0;" ::: "memory");
}
__device__ __forceinline__ void bulk_prefetch(const void* src, uint32_t bytes) { asm volatile("cp.async.bulk.prefetch.L2.global [%0], %1;" ::"l"(src), "r"(bytes) : "memory"); }
__device__ __forceinline__ void tma2d(uint32_t dst, const CUtensorMap* m, int c0, int c1, uint32_t bar) { asm volatile("cp.async.bulk.tensor.2d.shared::cluster.global.mbarrier::complete_tx::bytes [%0], [%1, {%3,%4}], [%2];" ::"r"(dst), "l"(m), "r"(bar), "r"(c0), "r"(c1) : "memory"); }
__device__ __forceinline__ void tma3d(uint32_t dst, const CUtensorMap* m, int c0, int c1, int c2, uint32_t bar) { asm volatile("cp.async.bulk.tensor.3d.shared::cluster.global.mbarrier::complete_tx::bytes [%0], [%1, {%3,%4,%5}], [%2];" ::"r"(dst), "l"(m), "r"(bar), "r"(c0), "r"(c1), "r"(c2) : "memory"); }
__device__ __forceinline__ void tma3d_mc(uint32_t dst, const CUtensorMap* m, int c0, int c1, int c2, uint32_t bar) { asm volatile("cp.async.bulk.tensor.3d.shared::cluster.global.mbarrier::complete_tx::bytes.multicast::cluster [%0], [%1, {%3,%4,%5}], [%2], %6;" ::"r"(dst), "l"(m), "r"(bar), "r"(c0), "r"(c1), "r"(c2), "h"((unsigned short)3) : "memory"); }
__device__ __forceinline__ void mbar_arrive_cl(uint32_t bar, uint32_t rank) { asm volatile("{ .reg .b32 ra; mapa.shared::cluster.u32 ra, %0, %1; mbarrier.arrive.shared::cluster.b64 _, [ra]; }" ::"r"(bar), "r"(rank) : "memory"); }
__device__ __forceinline__ int cta_index() { const int b = blockIdx.x; return (b & ~15) + (b & 1) * 8 + ((b >> 1) & 7); }
__device__ __forceinline__ void wg_fence() { asm volatile("wgmma.fence.sync.aligned;" ::: "memory"); }
__device__ __forceinline__ void wg_commit() { asm volatile("wgmma.commit_group.sync.aligned;" ::: "memory"); }
template <int N> __device__ __forceinline__ void wg_wait() { asm volatile("wgmma.wait_group.sync.aligned %0;" ::"n"(N) : "memory"); }
template <int N> __device__ __forceinline__ void reg_fence(float (&d)[N]) {
#pragma unroll
  for (int i = 0; i < N; i++) asm volatile("" : "+f"(d[i])::"memory");
}
__device__ __forceinline__ u64 dsc(uint32_t lo, uint32_t lbo, uint32_t sbo, uint32_t sw) { return (u64)(lo + ((lbo >> 4) << 16)) | ((u64)((sbo >> 4) | (sw << 30)) << 32); }
__device__ __forceinline__ void ldsm4(uint32_t (&r)[4], uint32_t addr) { asm volatile("ldmatrix.sync.aligned.m8n8.x4.shared.b16 {%0,%1,%2,%3}, [%4];" : "=r"(r[0]), "=r"(r[1]), "=r"(r[2]), "=r"(r[3]) : "r"(addr) : "memory"); }
__device__ __forceinline__ void ldsm4t(uint32_t (&r)[4], uint32_t addr) { asm volatile("ldmatrix.sync.aligned.m8n8.x4.trans.shared.b16 {%0,%1,%2,%3}, [%4];" : "=r"(r[0]), "=r"(r[1]), "=r"(r[2]), "=r"(r[3]) : "r"(addr) : "memory"); }
__device__ __forceinline__ void ldsm2t(uint32_t (&r)[2], uint32_t addr) { asm volatile("ldmatrix.sync.aligned.m8n8.x2.trans.shared.b16 {%0,%1}, [%2];" : "=r"(r[0]), "=r"(r[1]) : "r"(addr) : "memory"); }
__device__ __forceinline__ void stsm4(uint32_t addr, uint32_t a, uint32_t b, uint32_t c, uint32_t d) { asm volatile("stmatrix.sync.aligned.m8n8.x4.shared.b16 [%0], {%1,%2,%3,%4};" ::"r"(addr), "r"(a), "r"(b), "r"(c), "r"(d) : "memory"); }
__device__ __forceinline__ uint4 lds128(uint32_t addr) { uint4 v; asm volatile("ld.shared.v4.u32 {%0,%1,%2,%3}, [%4];" : "=r"(v.x), "=r"(v.y), "=r"(v.z), "=r"(v.w) : "r"(addr) : "memory"); return v; }
__device__ __forceinline__ float4 lds128f(uint32_t addr) { float4 v; asm volatile("ld.shared.v4.f32 {%0,%1,%2,%3}, [%4];" : "=f"(v.x), "=f"(v.y), "=f"(v.z), "=f"(v.w) : "r"(addr) : "memory"); return v; }
__device__ __forceinline__ float2 lds64f(uint32_t addr) { float2 v; asm volatile("ld.shared.v2.f32 {%0,%1}, [%2];" : "=f"(v.x), "=f"(v.y) : "r"(addr) : "memory"); return v; }
__device__ __forceinline__ float lds32f(uint32_t addr) { float v; asm volatile("ld.shared.f32 %0, [%1];" : "=f"(v) : "r"(addr) : "memory"); return v; }
__device__ __forceinline__ uint32_t lds32(uint32_t addr) { uint32_t v; asm volatile("ld.shared.u32 %0, [%1];" : "=r"(v) : "r"(addr) : "memory"); return v; }
__device__ __forceinline__ void sts32(uint32_t addr, uint32_t v) { asm volatile("st.shared.u32 [%0], %1;" ::"r"(addr), "r"(v) : "memory"); }
__device__ __forceinline__ void sts32f(uint32_t addr, float v) { asm volatile("st.shared.f32 [%0], %1;" ::"r"(addr), "f"(v) : "memory"); }
__device__ __forceinline__ void sts64(uint32_t addr, uint32_t a, uint32_t b) { asm volatile("st.shared.v2.u32 [%0], {%1,%2};" ::"r"(addr), "r"(a), "r"(b) : "memory"); }
__device__ __forceinline__ void sts128(uint32_t addr, uint4 v) { asm volatile("st.shared.v4.u32 [%0], {%1,%2,%3,%4};" ::"r"(addr), "r"(v.x), "r"(v.y), "r"(v.z), "r"(v.w) : "memory"); }
__device__ __forceinline__ uint32_t packbf(float lo, float hi) { uint32_t r; asm("cvt.rn.bf16x2.f32 %0, %1, %2;" : "=r"(r) : "f"(hi), "f"(lo)); return r; }
__device__ __forceinline__ uint32_t packtr(float lo, float hi) { return __byte_perm(__float_as_uint(lo), __float_as_uint(hi), 0x7632); }
__device__ __forceinline__ float bflo(uint32_t v) { return __uint_as_float(v << 16); }
__device__ __forceinline__ float bfhi(uint32_t v) { return __uint_as_float(v & 0xffff0000u); }
__device__ __forceinline__ float bfround(float x) { return bflo(packbf(x, 0.f)); }
__device__ __forceinline__ uint32_t hmul2(uint32_t a, uint32_t b) { uint32_t r; asm("mul.rn.bf16x2 %0, %1, %2;" : "=r"(r) : "r"(a), "r"(b)); return r; }
__device__ __forceinline__ uint32_t hfma2(uint32_t a, uint32_t b, uint32_t c) { uint32_t r; asm("fma.rn.bf16x2 %0, %1, %2, %3;" : "=r"(r) : "r"(a), "r"(b), "r"(c)); return r; }
__device__ __forceinline__ uint32_t hadd2(uint32_t a, uint32_t b) { uint32_t r; asm("add.rn.bf16x2 %0, %1, %2;" : "=r"(r) : "r"(a), "r"(b)); return r; }
__device__ __forceinline__ float ex2(float x) { float r; asm("ex2.approx.ftz.f32 %0, %1;" : "=f"(r) : "f"(x)); return r; }
__device__ __forceinline__ float bsel(uint32_t m, float x, float y) { return __uint_as_float((__float_as_uint(x) & m) | (__float_as_uint(y) & ~m)); }
__device__ __forceinline__ float rcpf(float x) { float r; asm("rcp.approx.ftz.f32 %0, %1;" : "=f"(r) : "f"(x)); return r; }
__device__ __forceinline__ float sel_le(int a, int b, float x, float y) { float r; asm("{ .reg .pred p; setp.le.s32 p, %1, %2; selp.f32 %0, %3, %4, p; }" : "=f"(r) : "r"(a), "r"(b), "f"(x), "f"(y)); return r; }
__device__ __forceinline__ void mma16(float (&d)[4], uint32_t a0, uint32_t a2, uint32_t b0, uint32_t b1) {
  asm volatile("mma.sync.aligned.m16n8k16.row.col.f32.bf16.bf16.f32 {%0,%1,%2,%3}, {%4,%5,%6,%5}, {%7,%8}, {%0,%1,%2,%3};" : "+f"(d[0]), "+f"(d[1]), "+f"(d[2]), "+f"(d[3]) : "r"(a0), "r"(0u), "r"(a2), "r"(b0), "r"(b1));
}
__device__ __forceinline__ void mma16f(float (&d)[4], uint32_t a0, uint32_t a1, uint32_t a2, uint32_t a3, uint32_t b0, uint32_t b1) {
  asm volatile("mma.sync.aligned.m16n8k16.row.col.f32.bf16.bf16.f32 {%0,%1,%2,%3}, {%4,%5,%6,%7}, {%8,%9}, {%0,%1,%2,%3};" : "+f"(d[0]), "+f"(d[1]), "+f"(d[2]), "+f"(d[3]) : "r"(a0), "r"(a1), "r"(a2), "r"(a3), "r"(b0), "r"(b1));
}
__device__ __forceinline__ uint4 ldg128(const void* p) { uint4 v; asm volatile("ld.global.nc.L1::no_allocate.v4.u32 {%0,%1,%2,%3}, [%4];" : "=r"(v.x), "=r"(v.y), "=r"(v.z), "=r"(v.w) : "l"(p)); return v; }
__device__ __forceinline__ uint2 ldg64(const void* p) { uint2 v; asm volatile("ld.global.nc.L1::no_allocate.v2.u32 {%0,%1}, [%2];" : "=r"(v.x), "=r"(v.y) : "l"(p)); return v; }
__device__ __forceinline__ void ll_st64(uint2* p, uint32_t a, uint32_t tag) { u64 v = (u64)a | ((u64)tag << 32); asm volatile("st.relaxed.gpu.global.b64 [%0], %1;" ::"l"(p), "l"(v) : "memory"); }
__device__ __forceinline__ void ll_st128(uint4* p, uint32_t a, uint32_t b, uint32_t c, uint32_t tag) {
  asm volatile("{ .reg .b128 v; .reg .b64 lo, hi; mov.b64 lo, {%1,%2}; mov.b64 hi, {%3,%4}; mov.b128 v, {lo,hi}; st.relaxed.gpu.global.b128 [%0], v; }" ::"l"(p), "r"(a), "r"(b), "r"(c), "r"(tag) : "memory");
}
__device__ __forceinline__ uint4 ll_ld128(const uint4* p) {
  uint4 r;
  asm volatile("{ .reg .b128 v; .reg .b64 lo, hi; ld.relaxed.gpu.global.b128 v, [%4]; mov.b128 {lo,hi}, v; mov.b64 {%0,%1}, lo; mov.b64 {%2,%3}, hi; }" : "=r"(r.x), "=r"(r.y), "=r"(r.z), "=r"(r.w) : "l"(p) : "memory");
  return r;
}
__device__ __forceinline__ uint4 ll_ld128_acq(const uint4* p) {
  uint4 r;
  asm volatile("{ .reg .b128 v; .reg .b64 lo, hi; ld.acquire.gpu.global.b128 v, [%4]; mov.b128 {lo,hi}, v; mov.b64 {%0,%1}, lo; mov.b64 {%2,%3}, hi; }" : "=r"(r.x), "=r"(r.y), "=r"(r.z), "=r"(r.w) : "l"(p) : "memory");
  return r;
}
__device__ __forceinline__ uint4 ll_wait128(const uint4* p, uint32_t tag) {
  uint4 r; int it = 0;
  do { r = ll_ld128(p); if (++it > SPIN_LIMIT) TRAP(); } while (r.w != tag);
  return r;
}
__device__ __forceinline__ uint2 ll_wait64x2(const uint2* p, uint32_t tag) {
  uint4 r; int it = 0;
  do { r = ll_ld128((const uint4*)p); if (++it > SPIN_LIMIT) TRAP(); } while (r.y != tag || r.w != tag);
  return make_uint2(r.x, r.z);
}
__device__ __forceinline__ uint32_t ll_wait64(const uint2* p, uint32_t tag) {
  u64 v; int it = 0;
  do { asm volatile("ld.relaxed.gpu.global.b64 %0, [%1];" : "=l"(v) : "l"(p) : "memory"); if (++it > SPIN_LIMIT) TRAP(); } while ((uint32_t)(v >> 32) != tag);
  return (uint32_t)v;
}
__device__ __forceinline__ void flag_set(unsigned* p, uint32_t tag) { asm volatile("st.relaxed.gpu.global.u32 [%0], %1;" ::"l"(p), "r"(tag) : "memory"); }
__device__ __forceinline__ uint32_t flag_get(const unsigned* p) { uint32_t v; asm volatile("ld.relaxed.gpu.global.u32 %0, [%1];" : "=r"(v) : "l"(p) : "memory"); return v; }
__device__ __forceinline__ uint32_t redux_max(uint32_t v) { uint32_t r; asm volatile("redux.sync.max.u32 %0, %1, 0xffffffff;" : "=r"(r) : "r"(v)); return r; }
__device__ __forceinline__ void cp16(uint32_t dst, const void* src) { asm volatile("cp.async.cg.shared.global [%0], [%1], 16;" ::"r"(dst), "l"(src) : "memory"); }
#define CPH ".L2::128B"
__device__ __forceinline__ void cp16p(uint32_t dst, const void* src) { asm volatile("cp.async.cg.shared.global" CPH " [%0], [%1], 16;" ::"r"(dst), "l"(src) : "memory"); }
__device__ __forceinline__ void cp8(uint32_t dst, const void* src) { asm volatile("cp.async.ca.shared.global [%0], [%1], 8;" ::"r"(dst), "l"(src) : "memory"); }
__device__ __forceinline__ void cp_arrive(uint32_t bar) { asm volatile("cp.async.mbarrier.arrive.noinc.shared::cta.b64 [%0];" ::"r"(bar) : "memory"); }
__device__ __forceinline__ void wg_rs192(float (&d)[96], uint32_t a0, uint32_t a1, uint32_t a2, uint32_t a3, uint64_t db, int sc){
  asm volatile("{ .reg .pred p; setp.ne.b32 p, %101, 0;\n wgmma.mma_async.sync.aligned.m64n192k16.f32.bf16.bf16 {%0, %1, %2, %3, %4, %5, %6, %7, %8, %9, %10, %11, %12, %13, %14, %15, %16, %17, %18, %19, %20, %21, %22, %23, %24, %25, %26, %27, %28, %29, %30, %31, %32, %33, %34, %35, %36, %37, %38, %39, %40, %41, %42, %43, %44, %45, %46, %47, %48, %49, %50, %51, %52, %53, %54, %55, %56, %57, %58, %59, %60, %61, %62, %63, %64, %65, %66, %67, %68, %69, %70, %71, %72, %73, %74, %75, %76, %77, %78, %79, %80, %81, %82, %83, %84, %85, %86, %87, %88, %89, %90, %91, %92, %93, %94, %95}, {%96,%97,%98,%99}, %100, p, 1, 1, 1; }"
   : "+f"(d[0]), "+f"(d[1]), "+f"(d[2]), "+f"(d[3]), "+f"(d[4]), "+f"(d[5]), "+f"(d[6]), "+f"(d[7]), "+f"(d[8]), "+f"(d[9]), "+f"(d[10]), "+f"(d[11]), "+f"(d[12]), "+f"(d[13]), "+f"(d[14]), "+f"(d[15]), "+f"(d[16]), "+f"(d[17]), "+f"(d[18]), "+f"(d[19]), "+f"(d[20]), "+f"(d[21]), "+f"(d[22]), "+f"(d[23]), "+f"(d[24]), "+f"(d[25]), "+f"(d[26]), "+f"(d[27]), "+f"(d[28]), "+f"(d[29]), "+f"(d[30]), "+f"(d[31]), "+f"(d[32]), "+f"(d[33]), "+f"(d[34]), "+f"(d[35]), "+f"(d[36]), "+f"(d[37]), "+f"(d[38]), "+f"(d[39]), "+f"(d[40]), "+f"(d[41]), "+f"(d[42]), "+f"(d[43]), "+f"(d[44]), "+f"(d[45]), "+f"(d[46]), "+f"(d[47]), "+f"(d[48]), "+f"(d[49]), "+f"(d[50]), "+f"(d[51]), "+f"(d[52]), "+f"(d[53]), "+f"(d[54]), "+f"(d[55]), "+f"(d[56]), "+f"(d[57]), "+f"(d[58]), "+f"(d[59]), "+f"(d[60]), "+f"(d[61]), "+f"(d[62]), "+f"(d[63]), "+f"(d[64]), "+f"(d[65]), "+f"(d[66]), "+f"(d[67]), "+f"(d[68]), "+f"(d[69]), "+f"(d[70]), "+f"(d[71]), "+f"(d[72]), "+f"(d[73]), "+f"(d[74]), "+f"(d[75]), "+f"(d[76]), "+f"(d[77]), "+f"(d[78]), "+f"(d[79]), "+f"(d[80]), "+f"(d[81]), "+f"(d[82]), "+f"(d[83]), "+f"(d[84]), "+f"(d[85]), "+f"(d[86]), "+f"(d[87]), "+f"(d[88]), "+f"(d[89]), "+f"(d[90]), "+f"(d[91]), "+f"(d[92]), "+f"(d[93]), "+f"(d[94]), "+f"(d[95]) : "r"(a0),"r"(a1),"r"(a2),"r"(a3),"l"(db),"r"(sc));
}
__device__ __forceinline__ void wg_rs48(float (&d)[24], uint32_t a0, uint32_t a1, uint32_t a2, uint32_t a3, uint64_t db, int sc){
  asm volatile("{ .reg .pred p; setp.ne.b32 p, %29, 0;\n wgmma.mma_async.sync.aligned.m64n48k16.f32.bf16.bf16 {%0, %1, %2, %3, %4, %5, %6, %7, %8, %9, %10, %11, %12, %13, %14, %15, %16, %17, %18, %19, %20, %21, %22, %23}, {%24,%25,%26,%27}, %28, p, 1, 1, 1; }"
   : "+f"(d[0]), "+f"(d[1]), "+f"(d[2]), "+f"(d[3]), "+f"(d[4]), "+f"(d[5]), "+f"(d[6]), "+f"(d[7]), "+f"(d[8]), "+f"(d[9]), "+f"(d[10]), "+f"(d[11]), "+f"(d[12]), "+f"(d[13]), "+f"(d[14]), "+f"(d[15]), "+f"(d[16]), "+f"(d[17]), "+f"(d[18]), "+f"(d[19]), "+f"(d[20]), "+f"(d[21]), "+f"(d[22]), "+f"(d[23]) : "r"(a0),"r"(a1),"r"(a2),"r"(a3),"l"(db),"r"(sc));
}
__device__ __forceinline__ void wg_rs64z(float (&d)[32], uint32_t a0, uint32_t a1, uint32_t a2, uint32_t a3, uint64_t db){
  asm volatile("{ .reg .pred p; setp.ne.b32 p, 0, 0;\n wgmma.mma_async.sync.aligned.m64n64k16.f32.bf16.bf16 {%0, %1, %2, %3, %4, %5, %6, %7, %8, %9, %10, %11, %12, %13, %14, %15, %16, %17, %18, %19, %20, %21, %22, %23, %24, %25, %26, %27, %28, %29, %30, %31}, {%32,%33,%34,%35}, %36, p, 1, 1, 0; }"
   : "=f"(d[0]), "=f"(d[1]), "=f"(d[2]), "=f"(d[3]), "=f"(d[4]), "=f"(d[5]), "=f"(d[6]), "=f"(d[7]), "=f"(d[8]), "=f"(d[9]), "=f"(d[10]), "=f"(d[11]), "=f"(d[12]), "=f"(d[13]), "=f"(d[14]), "=f"(d[15]), "=f"(d[16]), "=f"(d[17]), "=f"(d[18]), "=f"(d[19]), "=f"(d[20]), "=f"(d[21]), "=f"(d[22]), "=f"(d[23]), "=f"(d[24]), "=f"(d[25]), "=f"(d[26]), "=f"(d[27]), "=f"(d[28]), "=f"(d[29]), "=f"(d[30]), "=f"(d[31]) : "r"(a0),"r"(a1),"r"(a2),"r"(a3),"l"(db));
}
__device__ __forceinline__ void wg_rs64(float (&d)[32], uint32_t a0, uint32_t a1, uint32_t a2, uint32_t a3, uint64_t db){
  asm volatile("{ .reg .pred p; setp.ne.b32 p, 1, 0;\n wgmma.mma_async.sync.aligned.m64n64k16.f32.bf16.bf16 {%0, %1, %2, %3, %4, %5, %6, %7, %8, %9, %10, %11, %12, %13, %14, %15, %16, %17, %18, %19, %20, %21, %22, %23, %24, %25, %26, %27, %28, %29, %30, %31}, {%32,%33,%34,%35}, %36, p, 1, 1, 0; }"
   : "+f"(d[0]), "+f"(d[1]), "+f"(d[2]), "+f"(d[3]), "+f"(d[4]), "+f"(d[5]), "+f"(d[6]), "+f"(d[7]), "+f"(d[8]), "+f"(d[9]), "+f"(d[10]), "+f"(d[11]), "+f"(d[12]), "+f"(d[13]), "+f"(d[14]), "+f"(d[15]), "+f"(d[16]), "+f"(d[17]), "+f"(d[18]), "+f"(d[19]), "+f"(d[20]), "+f"(d[21]), "+f"(d[22]), "+f"(d[23]), "+f"(d[24]), "+f"(d[25]), "+f"(d[26]), "+f"(d[27]), "+f"(d[28]), "+f"(d[29]), "+f"(d[30]), "+f"(d[31]) : "r"(a0),"r"(a1),"r"(a2),"r"(a3),"l"(db));
}
__device__ __forceinline__ void wg_rs24(float (&d)[12], uint32_t a0, uint32_t a1, uint32_t a2, uint32_t a3, uint64_t db){
  asm volatile("{ .reg .pred p; setp.ne.b32 p, 1, 0;\n wgmma.mma_async.sync.aligned.m64n24k16.f32.bf16.bf16 {%0, %1, %2, %3, %4, %5, %6, %7, %8, %9, %10, %11}, {%12,%13,%14,%15}, %16, p, 1, 1, 1; }"
   : "+f"(d[0]), "+f"(d[1]), "+f"(d[2]), "+f"(d[3]), "+f"(d[4]), "+f"(d[5]), "+f"(d[6]), "+f"(d[7]), "+f"(d[8]), "+f"(d[9]), "+f"(d[10]), "+f"(d[11]) : "r"(a0),"r"(a1),"r"(a2),"r"(a3),"l"(db));
}
__device__ __forceinline__ void wg_rs80(float (&d)[40], uint32_t a0, uint32_t a1, uint32_t a2, uint32_t a3, uint64_t db){
  asm volatile("{ .reg .pred p; setp.ne.b32 p, 1, 0;\n wgmma.mma_async.sync.aligned.m64n80k16.f32.bf16.bf16 {%0, %1, %2, %3, %4, %5, %6, %7, %8, %9, %10, %11, %12, %13, %14, %15, %16, %17, %18, %19, %20, %21, %22, %23, %24, %25, %26, %27, %28, %29, %30, %31, %32, %33, %34, %35, %36, %37, %38, %39}, {%40,%41,%42,%43}, %44, p, 1, 1, 1; }"
   : "+f"(d[0]), "+f"(d[1]), "+f"(d[2]), "+f"(d[3]), "+f"(d[4]), "+f"(d[5]), "+f"(d[6]), "+f"(d[7]), "+f"(d[8]), "+f"(d[9]), "+f"(d[10]), "+f"(d[11]), "+f"(d[12]), "+f"(d[13]), "+f"(d[14]), "+f"(d[15]), "+f"(d[16]), "+f"(d[17]), "+f"(d[18]), "+f"(d[19]), "+f"(d[20]), "+f"(d[21]), "+f"(d[22]), "+f"(d[23]), "+f"(d[24]), "+f"(d[25]), "+f"(d[26]), "+f"(d[27]), "+f"(d[28]), "+f"(d[29]), "+f"(d[30]), "+f"(d[31]), "+f"(d[32]), "+f"(d[33]), "+f"(d[34]), "+f"(d[35]), "+f"(d[36]), "+f"(d[37]), "+f"(d[38]), "+f"(d[39]) : "r"(a0),"r"(a1),"r"(a2),"r"(a3),"l"(db));
}
constexpr uint32_t SMD = 1024;
constexpr uint32_t STAGE = 47104, CHB = 22528, GB = 2816;
constexpr uint32_t KVO = 94208, WO = 139264, WO7 = 112640, MOEW = 30720;
constexpr uint32_t TAB1 = 188416, T_SA = TAB1, T_C1 = TAB1 + 1280, T_RED = TAB1 + 4224, T_SIL = TAB1 + 6528, T_CR = TAB1 + 7808, T_W = TAB1 + 9216;
constexpr uint32_t TAB2 = 228864, T_EA = TAB2, T_EB = TAB2 + 1280, T_SC = TAB2 + 1920, T_KEY = TAB2 + 1984, T_TAG = TAB2 + 2048, BARS = TAB2 + 2112;
constexpr uint32_t T_X = 3 * STAGE, T_XR = 0, T_MRED = 22528;
constexpr uint32_t SMEM_BYTES = TAB2 + 2816;
enum { B_FULL = 0, B_KV4 = 4, B_WO = 5, B_PRM2 = 6, B_C1 = 7, B_XR = 8, B_MOEW = 9, B_ONE = 10, B_EMPTY = 10, B_GEMM = 14, B_OD = 15, B_EPI1 = 16, B_ATT = 17, B_KVN = 18, B_NUM = 22 };

#define ASTAMP(i) STAMP(i)
#define OD 2
#define AUXGO B_GEMM
#define DELAY_A 2500
#define PZ 1
#define TMAFIRST 3
struct Params {
  CUtensorMap mx, mw64, mw16, mwo, mxr, mwg, mwu, mwd;
  const __nv_bfloat16 *x, *wqkv, *wo, *wr, *wg, *wu, *wd, *c, *wmod;
  __nv_bfloat16* out;
};

__device__ __forceinline__ float silu_f(float v) { return v * rcpf(1.f + ex2(v * -1.4426950408889634f)); }
__device__ __forceinline__ uint32_t slab_off(int row, int half) { return row * 32 + ((half ^ ((row >> 2) & 1)) << 4); }
__device__ __forceinline__ void slab_mma(float (&d)[2][4], uint32_t slab, int ks, int lane, uint32_t a0, uint32_t a2) {
  uint32_t b[4];
  ldsm4t(b, slab + slab_off(ks * 16 + (lane & 15), lane >> 4));
  mma16(d[0], a0, a2, b[0], b[1]); mma16(d[1], a0, a2, b[2], b[3]);
}
__device__ __forceinline__ uint32_t vec_off(int ks, int q) { return (ks >> 1) * 64 + q * 16 + (ks & 1) * 8; }

__device__ __forceinline__ void issue_qk(float (&s)[32], const uint32_t (&q)[8], uint32_t cb, int h) {
  const uint32_t pb = cb + (h >> 1) * 88;
  wg_rs64z(s, q[0], q[1], q[2], q[3], dsc(pb + ((h & 1) ? 24 : 0), 128, GB, 0));
  wg_rs64(s, q[4], q[5], q[6], q[7], dsc(pb + 16, 640, GB, 0));
}
__device__ __forceinline__ void issue_pv1(float (&o)[12], const uint32_t (&p)[16], uint32_t cb, int h, int b) {
  wg_rs24(o, p[4 * b], p[4 * b + 1], p[4 * b + 2], p[4 * b + 3], dsc(cb + (h >> 1) * 88 + 40 + (h & 1) * 24 + b * (2 * GB / 16), GB, 128, 0));
}
__device__ __forceinline__ uint32_t sortable(float r) { uint32_t u = __float_as_uint(r); return (u & 0x80000000u) ? ~u : (u | 0x80000000u); }
__device__ __forceinline__ float unsortable(uint32_t k) { return __uint_as_float((k & 0x80000000u) ? (k & 0x7fffffffu) : ~k); }
__device__ __forceinline__ void top2(uint32_t a, uint32_t b, uint32_t& k1, uint32_t& k2) {
  k1 = redux_max(max(a, b));
  k2 = redux_max(max(a == k1 ? 0u : a, b == k1 ? 0u : b));
}

__device__ __noinline__ void exact_row_max(uint32_t (&q)[4][8], uint32_t sm, int wg, int m, int dd) {
  const int lane = threadIdx.x & 31, q4 = lane & 3;
#pragma unroll 1
  for (int h = 0; h < 4; h++) {
    float mx[2] = {-3e38f, -3e38f};
    const uint32_t lo = (h >> 1) * 1408 + (lane & 7) * 16 + ((lane >> 4) ? 256 : ((h & 1) ? 384 : 0) + ((lane >> 3) & 1) * 128);
#pragma unroll 1
    for (int n = max(0, 4 - 2 * m - wg) * 8; n < 40; n++) {
      const int j = wg + (n >> 3);
      uint32_t k[4]; float s[4] = {0.f, 0.f, 0.f, 0.f};
      ldsm4(k, sm + (j < 4 ? j * CHB : KVO + (j - 4) * CHB) + (n & 7) * GB + lo);
      mma16f(s, q[h][0], q[h][1], q[h][2], q[h][3], k[0], k[1]); mma16f(s, q[h][4], q[h][5], 0u, 0u, k[2], 0u);
#pragma unroll
      for (int e = 0; e < 4; e++) {
        const int d = 8 * n + (e & 1) - (e >> 1) * 8 - dd;
        if (d > 0 && d <= 256) mx[e >> 1] = fmaxf(mx[e >> 1], s[e]);
      }
    }
#pragma unroll
    for (int r = 0; r < 2; r++) {
      float x = mx[r];
      x = fmaxf(x, __shfl_xor_sync(~0u, x, 1)); x = fmaxf(x, __shfl_xor_sync(~0u, x, 2));
      const float a = bfround(-x), b = bfround(-x - a), c = -x - a - b;
      q[h][6 + r] = q4 == 2 ? packbf(a, b) : (q4 == 3 ? packbf(c, 0.f) : 0u);
    }
  }
}

__device__ __noinline__ void aux_mod(const Params& P, uint32_t sm, uint32_t tag) {
  const int tid = threadIdx.x, lane = tid & 31, warp = tid >> 5, cta = blockIdx.x, m = cta >> 3, g = cta & 7;
  auto bar = [&](int i) { return sm + BARS + 8 * i; };
      const int t = tid - 288, aw = warp - 9;
      const int hf = t & 1;
      auto load_slab = [&](const __nv_bfloat16* base) {
#pragma unroll 1
        for (int i = t; i < 1280; i += 96) cp16(sm + T_W + i * 16, base + (i >> 1) * 3840 + hf * 8);
      };
      int G = cta < 80 ? 128 + cta : cta;
      auto reset_slots = [&]() {
#pragma unroll 1
      for (int i = t; i < 548; i += 96) {
        const int k = i - 128, r = k / 40, c = k - r * 40;
        uint4* p = i < 128 ? &g_part[cta * 128 + i] : (r < 8 ? g_h2 + r * 5120 : g_x2) + ((m * 2 + (c >= 20)) * 8 + g) * 20 + (c >= 20 ? c - 20 : c);
        if (k >= 360) p = k < 376 ? &g_keys[((g * 8 + ((k >> 1) & 7)) * 16 + m) * 2 + (k & 1)] : k < 408 ? &g_gu[((k >> 3) & 3) * 768 + (cta < 96 ? cta : 0) * 8 + (k & 7)] : (uint4*)&g_mod[(k < 416 ? G : G + 128) * 8] + (k & 3);
        if (k < 376 || (k < 408 ? cta < 96 : k >= 412 && (k < 416 || (cta >= 80 && cta < 112)))) ll_st128(p, 0u, 0u, 0u, 0u);
      }
      };
      load_slab(P.wmod + G * 16);
      reset_slots();
#pragma unroll 1
      for (;; G += 128) {
        asm volatile("cp.async.wait_all;" ::: "memory");
        float a[8] = {0.f, 0.f, 0.f, 0.f, 0.f, 0.f, 0.f, 0.f};
#pragma unroll 1
        for (int i = t; i < 1280; i += 96) {
          const uint4 w = lds128(sm + T_W + i * 16);
          const uint32_t sp = lds32(sm + T_SIL + (i & ~3));
          const float sv = (i & 2) ? bfhi(sp) : bflo(sp);
          a[0] = fmaf(sv, bflo(w.x), a[0]); a[1] = fmaf(sv, bfhi(w.x), a[1]); a[2] = fmaf(sv, bflo(w.y), a[2]); a[3] = fmaf(sv, bfhi(w.y), a[3]);
          a[4] = fmaf(sv, bflo(w.z), a[4]); a[5] = fmaf(sv, bfhi(w.z), a[5]); a[6] = fmaf(sv, bflo(w.w), a[6]); a[7] = fmaf(sv, bfhi(w.w), a[7]);
        }
        if (G < 112) load_slab(P.wmod + (G + 128) * 16);
        {
          const bool u = lane & 16, v = lane & 8;
#pragma unroll
          for (int i = 0; i < 4; i++) a[i] = (u ? a[i + 4] : a[i]) + __shfl_xor_sync(~0u, u ? a[i] : a[i + 4], 16);
#pragma unroll
          for (int i = 0; i < 2; i++) a[i] = (v ? a[i + 2] : a[i]) + __shfl_xor_sync(~0u, v ? a[i] : a[i + 2], 8);
#pragma unroll
          for (int o = 4; o >= 2; o >>= 1) { a[0] += __shfl_xor_sync(~0u, a[0], o); a[1] += __shfl_xor_sync(~0u, a[1], o); }
          if (!(lane & 6)) sts64(sm + T_RED + (G & 128) * 2 + aw * 64 + hf * 32 + (lane >> 3) * 8, __float_as_uint(a[0]), __float_as_uint(a[1]));
        }
        bar_sync(4, 96);
        if (t < 8) {
          const uint32_t ad = sm + T_RED + (G & 128) * 2 + t * 8;
          const float2 a0 = lds64f(ad), a1 = lds64f(ad + 64), a2 = lds64f(ad + 128);
          ll_st64(&g_mod[G * 8 + t], packbf(a0.x + a1.x + a2.x, a0.y + a1.y + a2.y), tag);
        }
        if (G >= 112) break;
      }
      if (t == 0) g_prof_set(30);
      if (t == 32) {
        bulk_prefetch(P.wo + cta * 3200, 6400);
        bulk_prefetch(P.wg + cta * 7680, 15360); bulk_prefetch(P.wu + cta * 7680, 15360); bulk_prefetch(P.wd + cta * 7680, 15360);
      }
      __syncwarp();
      if (t == 0) mbar_arrive(bar(B_EPI1));
}
__device__ __noinline__ void aux_late(const Params& P, uint32_t sm, uint32_t tag) {
  const int tid = threadIdx.x, lane = tid & 31, warp = tid >> 5, cta = blockIdx.x, m = cta >> 3, g = cta & 7;
  auto bar = [&](int i) { return sm + BARS + 8 * i; };
    if (warp == 8) {
      mbar_wait(bar(B_EPI1), 0);
      if (lane == 0) mbar_expect_tx(bar(B_WO), 7 * 12800);
      __syncwarp();
      if (lane < 7) tma3d(sm + WO + lane * 12800, &P.mwo, 0, ((g + lane) & 7) * 80, g * 5, bar(B_WO));
      __syncwarp();
      mbar_wait(bar(B_ATT), 0);
      if (lane == 0) {
        mbar_expect_tx(bar(B_XR), 12800 + 20480);
        tma3d(sm + WO7, &P.mwo, 0, ((g + 7) & 7) * 80, g * 5, bar(B_XR));
        tma2d(sm + T_XR, &P.mxr, g * 80, m * 128, bar(B_XR));
        mbar_expect_tx(bar(B_MOEW), cta < 96 ? 40960 : 73728);
      }
      __syncwarp();
      mbar_wait(bar(B_OD), 0);
      if (cta < 96) { if (lane < 8) tma2d(sm + MOEW + lane * 5120, (lane & 4) ? &P.mwu : &P.mwg, cta * 16, (lane & 3) * 160, bar(B_MOEW)); }
      else if (lane < 6) tma2d(sm + MOEW + lane * 12288, &P.mwd, ((cta - 96) * 20) & ~7, lane * 256, bar(B_MOEW));
    } else {
      if (warp == 11) {
        float U = 0.f, Bc = 0.f;
        if (lane < 20) {
          const uint4* mp = (const uint4*)&g_mod[640 + g * 40 + lane * 2];
          const uint2 wr2 = ldg64(P.wr + g * 80 + lane * 4);
          uint4 ga, sb, cb, gb; int it = 0;
          do {
            ga = ll_ld128(mp); sb = ll_ld128(mp + 160); cb = ll_ld128(mp + 320); gb = ll_ld128(mp + 480);
            if (++it > SPIN_LIMIT) TRAP();
          } while (((ga.y ^ tag) | (ga.w ^ tag) | (sb.y ^ tag) | (sb.w ^ tag) | (cb.y ^ tag) | (cb.w ^ tag) | (gb.y ^ tag) | (gb.w ^ tag)) != 0u);
#pragma unroll
          for (int i = 0; i < 2; i++) {
            const uint32_t c2 = hadd2(i ? cb.z : cb.x, 0x3f803f80u), wr = i ? wr2.y : wr2.x, s = i ? sb.z : sb.x, a = i ? ga.z : ga.x, ad = sm + lane * 32 + i * 16;
            const float w0 = bflo(c2) * bflo(wr), w1 = bfhi(c2) * bfhi(wr);
            const uint32_t wh = packbf(w0, w1);
            U += w0 + w1; Bc = fmaf(bflo(s), bflo(wr), fmaf(bfhi(s), bfhi(wr), Bc));
            sts128(ad + T_EA, make_uint4(a, 0x3f803f80u, 0u, 0u));
            sts128(ad + T_EA + 640, make_uint4(a, wh, packbf(w0 - bflo(wh), w1 - bfhi(wh)), 0u));
            sts128(ad + T_EB, make_uint4(c2, s, i ? gb.z : gb.x, 0u));
          }
        }
        __syncwarp();
#pragma unroll
        for (int o = 16; o; o >>= 1) { U += __shfl_xor_sync(~0u, U, o); Bc += __shfl_xor_sync(~0u, Bc, o); }
        if (lane < 2) ll_st128(&g_rc[cta * 2 + lane], __float_as_uint(U), __float_as_uint(Bc), 0u, tag);
        uint4 v; int it = 0;
        do { v = ll_ld128(&g_rc[(m * 8 + (lane & 7)) * 2]); if (++it > SPIN_LIMIT) TRAP(); } while (v.w != tag);
        __syncwarp();
        U = __uint_as_float(v.x); Bc = __uint_as_float(v.y);
#pragma unroll
        for (int o = 4; o; o >>= 1) { U += __shfl_xor_sync(~0u, U, o); Bc += __shfl_xor_sync(~0u, Bc, o); }
        if (lane == 0) { sts64(sm + T_SC, __float_as_uint(U), __float_as_uint(Bc)); mbar_arrive(bar(B_PRM2)); g_prof_set(31); }
      }
    }
}

__global__ void __launch_bounds__(384, 1) fused_kernel(const __nv_bfloat16* __restrict__ px, const __nv_bfloat16* __restrict__ pwmod, const __nv_bfloat16* __restrict__ pc, const __grid_constant__ Params P) {
  extern __shared__ __align__(1024) unsigned char smem_raw[];
  const long long t_start = clock64();
  const uint32_t sm = smem_u32(smem_raw);
  const int tid = threadIdx.x, lane = tid & 31;
  const int warp = __shfl_sync(~0u, tid >> 5, 0);
  const int cta = blockIdx.x, m = cta >> 3, g = cta & 7;
  uint32_t tag;
  auto bar = [&](int i) { return sm + BARS + 8 * i; };
  if (tid == 288) {
    asm volatile("ld.relaxed.gpu.global.u32 %0, [%1];" : "=r"(tag) : "l"(&g_epoch[g * 32]) : "memory");
    tag++;
    sts32(sm + T_TAG, tag + ((tag & 0xffffu) == 0u) * 2);
  } else if (tid >= 256) {
    if (tid == 256) {
      if ((sm & 0xffffffu) != SMD) TRAP();
#pragma unroll 1
      for (int i = 0; i < B_NUM; i++) mbar_init(bar(i), i < B_ONE ? 1 : i < B_EPI1 ? 8 : i == B_EPI1 ? 9 : i == B_ATT ? 2 : 4);
      asm volatile("fence.mbarrier_init.release.cluster;" ::: "memory");
      fence_async_smem();
    }
  } else {
    const int w = tid >> 5;
    if (tid < 80) cp16(sm + T_SIL + tid * 16, pc + tid * 8);
    asm volatile("cp.async.commit_group;" ::: "memory");
#pragma unroll
    for (int i = 0; i < 5; i++) cp16(sm + T_X + (tid >> 4) * 1296 + (lane & 15) * 16 + i * 256, px + (cta * 16 + (tid >> 4)) * 640 + i * 128 + (lane & 15) * 8);
    if (cta < 80) {
      const int r = w * 80 + (lane >> 1);
      const __nv_bfloat16* src = pwmod + r * 3840 + cta * 16 + (lane & 1) * 8;
#pragma unroll
      for (int i = 0; i < 5; i++) cp16p(sm + T_W + slab_off(r, lane & 1) + i * 512, src + i * (16 * 3840));
    }
    asm volatile("cp.async.commit_group;" ::: "memory");
  }
  __syncwarp();
  if (warp < 8) {
    const int wg = warp >> 2, wl = warp & 3, gq = lane >> 2, q4 = lane & 3;
    uint32_t rs0, rs1, nm0, nm1; float fx0, fx1; uint4* xch;
    {
      uint2* pub = tid >= 64 ? &g_stat[cta * 16 + (tid & 15)] : &g_modr[(tid >> 3) * 640 + cta * 8 + (tid & 7)];
      const bool pubs = tid < 80 && (tid >= 64 || cta < 80);
      if (pubs) ll_st64(pub, 0u, 0u);
      if (tid < 80) {
        asm volatile("cp.async.wait_group 1;" ::: "memory");
        STAMP(20);
        const uint4 c4 = lds128(sm + T_SIL + tid * 16);
        sts128(sm + T_SIL + tid * 16, make_uint4(packbf(silu_f(bflo(c4.x)), silu_f(bfhi(c4.x))), packbf(silu_f(bflo(c4.y)), silu_f(bfhi(c4.y))), packbf(silu_f(bflo(c4.z)), silu_f(bfhi(c4.z))), packbf(silu_f(bflo(c4.w)), silu_f(bfhi(c4.w)))));
      }
      asm volatile("cp.async.wait_all;" ::: "memory");
      if (wg == 0) STAMP(35);
      bar_sync(0, 384);
      tag = lds32(sm + T_TAG);
      xch = g_xch + lane;
      if (lane >= 30) { ll_st128(xch + cta * 4096 + warp * 352 + 320, 0u, 0u, 0u, ~tag); ll_st128(xch + cta * 4096 + 2816 + warp * 160 + 128, 0u, 0u, 0u, ~tag); }
      if (wg == 0) STAMP(22);
      {
        float sa[4] = {0.f, 0.f, 0.f, 0.f}, sc[4] = {0.f, 0.f, 0.f, 0.f}, sd[4] = {0.f, 0.f, 0.f, 0.f};
#pragma unroll
        for (int s = 0; s < 5; s++) {
          uint32_t r[4];
          ldsm4(r, sm + T_X + (lane & 15) * 1296 + (lane >> 4) * 16 + warp * 160 + s * 32);
          mma16f(sa, r[0], r[1], r[2], r[3], 0x3f803f80u, 0x3f803f80u); mma16f(sc, r[0], r[1], r[2], r[3], r[0], r[2]); mma16f(sd, r[0], r[1], r[2], r[3], r[1], r[3]);
        }
        if (q4 == (gq >> 1)) sts128(sm + T_RED + 512 + warp * 128 + gq * 16, make_uint4(__float_as_uint(sa[0]), __float_as_uint((gq & 1) ? sc[1] : sc[0]), __float_as_uint(sa[2]), __float_as_uint((gq & 1) ? sd[3] : sd[2])));
      }
      if (cta < 80) {
        const uint32_t a0 = lds32(sm + T_SIL + warp * 160 + gq * 32 + q4 * 4), a2 = lds32(sm + T_SIL + warp * 160 + gq * 32 + 16 + q4 * 4);
        float d[2][4] = {{0.f, 0.f, 0.f, 0.f}, {0.f, 0.f, 0.f, 0.f}};
#pragma unroll
        for (int s = 0; s < 5; s++) slab_mma(d, sm + T_W, warp * 5 + s, lane, gq == s ? a0 : 0u, gq == s ? a2 : 0u);
        const bool up = gq & 1;
        float v0 = (up ? d[1][0] : d[0][0]) + __shfl_xor_sync(~0u, up ? d[0][0] : d[1][0], 4), v1 = (up ? d[1][1] : d[0][1]) + __shfl_xor_sync(~0u, up ? d[0][1] : d[1][1], 4);
        v0 += __shfl_xor_sync(~0u, v0, 8); v1 += __shfl_xor_sync(~0u, v1, 8);
        v0 += __shfl_xor_sync(~0u, v0, 16); v1 += __shfl_xor_sync(~0u, v1, 16);
        if (lane < 8) sts64(sm + T_RED + warp * 64 + lane * 8, __float_as_uint(v0), __float_as_uint(v1));
      }
      if (wg == 0) STAMP(21);
      bar_sync(1, 256);
      if (pubs) {
        const bool st = tid >= 64;
        const uint32_t ad = sm + T_RED + (st ? 512 + (tid & 15) * 8 : (tid & 7) * 8);
        float s0 = 0.f, s1 = 0.f;
#pragma unroll
        for (int w2 = 0; w2 < 8; w2++) { float2 t = lds64f(ad + w2 * (st ? 128 : 64)); s0 += t.x; s1 += t.y; }
        if (st) {
          const float mean = s0 * (1.f / 640.f), rs = rsqrtf(fmaxf(fmaf(-mean, mean, s1 * (1.f / 640.f)), 0.f) + 1e-5f);
          ll_st64(pub, __float_as_uint(rs), __byte_perm(packbf(0.f, -mean * bfround(rs)), tag, 0x3254));
        } else ll_st64(pub, packbf(s0, s1), tag);
      }
      STAMP(0);
      asm volatile("setmaxnreg.inc.sync.aligned.u32 232;");
      {
        const uint4* pa = (const uint4*)&g_modr[g * 640 + 2 * tid];
        const uint4* pb = (const uint4*)&g_modr[g * 640 + 512 + 2 * (tid & 63)];
        const uint4* ps = (const uint4*)&g_stat[(m * 8 + warp) * 16 + gq * 2];
        uint4 va, vb, vs; int it = 0;
        vb.y = tag; vb.w = tag;
        do {
          va = ll_ld128(pa); vs = ll_ld128(ps);
          if (warp < 2) vb = ll_ld128(pb);
          if (++it > SPIN_LIMIT) TRAP();
        } while (va.y != tag || va.w != tag || vb.y != tag || vb.w != tag || (((vs.y ^ tag) | (vs.w ^ tag)) & 0xffffu));
        const int p = 2 * tid;
        const uint32_t ad = sm + T_SA + ((p & ~15) + (p & 3) * 4 + ((p >> 2) & 3)) * 4, one = tid < 160 ? 0u : 0x3f803f80u;
        sts32(ad, hadd2(va.x, one)); sts32(ad + 16, hadd2(va.z, one));
        if (warp < 2) { sts32(ad + 2048, hadd2(vb.x, 0x3f803f80u)); sts32(ad + 2064, hadd2(vb.z, 0x3f803f80u)); }
        fx0 = __uint_as_float(vs.x); fx1 = __uint_as_float(vs.z);
        rs0 = packbf(fx0, fx0); nm0 = __byte_perm(vs.y, 0, 0x3232); rs1 = packbf(fx1, fx1); nm1 = __byte_perm(vs.w, 0, 0x3232);
        fx0 *= rcpf(bfhi(rs0)); fx1 *= rcpf(bfhi(rs1));
      }
      bar_sync(1, 256);
      if (tid == 0) mbar_arrive(bar(B_C1));
      STAMP(1);
    }
    uint32_t q[4][8];
    {
      float d1[96], d2[24];
#pragma unroll
      for (int i = 0; i < 96; i++) asm volatile("" : "=f"(d1[i]));
#pragma unroll
      for (int i = 0; i < 24; i++) asm volatile("" : "=f"(d2[i]));
      const uint32_t arow = (warp * 16 + (lane & 15)) * 128, asw = lane & 7, ahi = lane >> 4;
      uint32_t f[2][16];
      uint32_t xa[4][4]; uint4 cf[2], sf[2];
      auto fetch_a = [&](int c) {
        const uint32_t st = sm + (c & 3) * STAGE;
        mbar_wait(bar(B_FULL + (c & 3)), (c >> 2) & 1);
#pragma unroll
        for (int k = 0; k < 4; k++) ldsm4(xa[k], st + arow + (((2 * k + ahi) ^ asw) << 4));
#pragma unroll
        for (int k2 = 0; k2 < 2; k2++) { cf[k2] = lds128(sm + T_C1 + (c * 2 + k2) * 64 + q4 * 16); sf[k2] = lds128(sm + T_SA + (c * 2 + k2) * 64 + q4 * 16); }
      };
      auto mod_a = [&](uint32_t (&fr)[16], int k2) {
        const uint32_t (&r0)[4] = xa[2 * k2]; const uint32_t (&r1)[4] = xa[2 * k2 + 1];
        fr[8 * k2 + 0] = hfma2(hfma2(r0[0], rs0, nm0), cf[k2].x, sf[k2].x); fr[8 * k2 + 1] = hfma2(hfma2(r0[1], rs1, nm1), cf[k2].x, sf[k2].x);
        fr[8 * k2 + 2] = hfma2(hfma2(r0[2], rs0, nm0), cf[k2].y, sf[k2].y); fr[8 * k2 + 3] = hfma2(hfma2(r0[3], rs1, nm1), cf[k2].y, sf[k2].y);
        fr[8 * k2 + 4] = hfma2(hfma2(r1[0], rs0, nm0), cf[k2].z, sf[k2].z); fr[8 * k2 + 5] = hfma2(hfma2(r1[1], rs1, nm1), cf[k2].z, sf[k2].z);
        fr[8 * k2 + 6] = hfma2(hfma2(r1[2], rs0, nm0), cf[k2].w, sf[k2].w); fr[8 * k2 + 7] = hfma2(hfma2(r1[3], rs1, nm1), cf[k2].w, sf[k2].w);
#pragma unroll
        for (int i = 0; i < 8; i++) asm volatile("" : "+r"(fr[8 * k2 + i]));
      };
      auto step = [&](const uint32_t (&fr)[16], uint32_t (&fn)[16], int c, bool more) {
        const uint32_t st = (SMD + (c & 3) * STAGE) >> 4;
        if (more) fetch_a(c + 1);
#pragma unroll
        for (int ks = 0; ks < 4; ks++) {
          wg_fence();
          wg_rs192(d1, fr[4 * ks], fr[4 * ks + 1], fr[4 * ks + 2], fr[4 * ks + 3], dsc(st + 1024 + ks * 128, 8192, 1024, 1), ks ? 1 : c);
          wg_rs48(d2, fr[4 * ks], fr[4 * ks + 1], fr[4 * ks + 2], fr[4 * ks + 3], dsc(st + 2560 + ks * 32, 2048, 256, 3), ks ? 1 : c);
          if (ks == 0) {
            wg_commit(); wg_wait<1>();
            if (c > 0 && lane == 0) mbar_arrive(bar(B_EMPTY + ((c - 1) & 3)));
          } else if (ks < 3) mod_a(fn, ks - 1);
        }
        wg_commit();
      };
      fetch_a(0); mod_a(f[0], 0); mod_a(f[0], 1);
      if (wg == 0) STAMP(23);
#pragma unroll 1
      for (int c = 0; c < 10; c += 2) {
        step(f[0], f[1], c, true);
        step(f[1], f[0], c + 1, c < 8);
      }
      if (wg == 0) STAMP(24);
      mbar_wait(bar(B_EMPTY + 2), 1);
      wg_wait<0>();
      reg_fence(d1); reg_fence(d2);
      if (lane == 0) mbar_arrive(bar(B_GEMM));
      STAMP(2 + wg);
      const float qs = 0.22360679774997896f * 1.4426950408889634f;
      auto fin = [&](int seg, int t, float (&v)[4]) {
        const float f0 = seg ? fx0 : fx0 * qs, f1 = seg ? fx1 : fx1 * qs;
        const float* a = t < 8 ? &d1[(seg * 8 + t) * 4] : &d2[(seg * 2 + t - 8) * 4];
        v[0] = a[0] * f0; v[1] = a[1] * f0; v[2] = a[2] * f1; v[3] = a[3] * f1;
      };
      const uint32_t kvl = sm + wl * (2 * GB) + ((lane >> 3) & 1) * GB + (lane >> 4) * 128 + (lane & 7) * 16;
      uint32_t mt[22][2];
      {
#pragma unroll
        for (int pr = 0; pr < 2; pr++) {
#pragma unroll
          for (int t = 0; t < 5; t++) { float v[4]; fin(1, pr * 5 + t, v); mt[pr * 11 + t][0] = packbf(v[0], v[1]); mt[pr * 11 + t][1] = packbf(v[2], v[3]); }
#pragma unroll
          for (int t = 0; t < 5; t++) {
            float v[4]; fin(2, pr * 5 + t, v);
            const uint32_t a = packbf(v[0], v[1]), b = packbf(v[2], v[3]);
            if (t < 2) { mt[pr * 11 + 5 + t][0] = a; mt[pr * 11 + 5 + t][1] = b; }
            else if (t > 2) { mt[pr * 11 + 6 + t][0] = a; mt[pr * 11 + 6 + t][1] = b; }
            else {
              const uint32_t c0 = q4 == 2 ? 0x3f803f80u : 0x00003f80u, c1 = q4 == 0 ? 0x00003f80u : 0u;
              mt[pr * 11 + 7][0] = q4 < 2 ? a : c0; mt[pr * 11 + 7][1] = q4 < 2 ? b : c0; mt[pr * 11 + 8][0] = q4 < 2 ? c1 : a; mt[pr * 11 + 8][1] = q4 < 2 ? c1 : b;
            }
          }
        }
#pragma unroll
        for (int v = 0; v < 11; v++) { mt[2 * v + 1][1] = (mt[2 * v + 1][1] & ~1u) | (tag & 1u); ll_st128(xch + cta * 4096 + warp * 352 + v * 32, mt[2 * v][0], mt[2 * v][1], mt[2 * v + 1][0], mt[2 * v + 1][1]); asm volatile("and.b32 %0, %0, -2;" : "+r"(mt[2 * v + 1][1])); }
      }
      if (wg == 0) STAMP(25);
#pragma unroll
      for (int pr = 0; pr < 2; pr++) {
        uint32_t qp[5][2];
#pragma unroll
        for (int t = 0; t < 5; t++) { float v[4]; fin(0, pr * 5 + t, v); qp[t][0] = packbf(v[0], v[1]); qp[t][1] = packbf(v[2], v[3]); }
        uint32_t (&qe)[8] = q[2 * pr]; uint32_t (&qo)[8] = q[2 * pr + 1];
        qe[0] = qp[0][0]; qe[1] = qp[0][1]; qe[2] = qp[1][0]; qe[3] = qp[1][1];
        qo[0] = qp[3][0]; qo[1] = qp[3][1]; qo[2] = qp[4][0]; qo[3] = qp[4][1];
        qe[4] = q4 < 2 ? qp[2][0] : 0u; qe[5] = q4 < 2 ? qp[2][1] : 0u; qo[4] = q4 < 2 ? 0u : qp[2][0]; qo[5] = q4 < 2 ? 0u : qp[2][1];
#pragma unroll
        for (int hh = 0; hh < 2; hh++) {
          uint32_t (&qh)[8] = q[2 * pr + hh];
          const int ka = pr * 11 + hh * 3;
          float lo[4] = {0.f, 0.f, 0.f, 0.f}, hi[4] = {0.f, 0.f, 0.f, 0.f};
          mma16f(lo, qh[0], qh[1], qh[2], qh[3], mt[ka][0], mt[ka + 1][0]); mma16f(hi, qh[0], qh[1], qh[2], qh[3], mt[ka][1], mt[ka + 1][1]);
          mma16f(lo, qh[4], qh[5], 0u, 0u, mt[pr * 11 + 2][0], 0u); mma16f(hi, qh[4], qh[5], 0u, 0u, mt[pr * 11 + 2][1], 0u);
          const uint32_t dg = __shfl_sync(~0u, packbf(-((gq & 1) ? lo[1] : lo[0]), -((gq & 1) ? hi[3] : hi[2])), (lane & ~3) | (gq >> 1));
          qh[6] = q4 == 2 ? dg & 0xffffu : 0u; qh[7] = q4 == 2 ? dg >> 16 : 0u;
        }
      }
#pragma unroll
        for (int v = 0; v < 11; v++) stsm4(kvl + KVO + wg * CHB + v * 256, mt[2 * v][0], mt[2 * v][1], mt[2 * v + 1][0], mt[2 * v + 1][1]);
        fence_async_smem();
      bar_sync(2 + wg, 128);
      if (tid == 0) mbar_arrive(bar(B_KV4));
      if (lane == 0) mbar_arrive(bar(B_EPI1));
      STAMP(4 + wg);
      if (wg == 0 && m > 0) {
        const uint4* sa = xch + (cta - 8) * 4096 + 1408 + wl * 352;
        int it = 0;
        while ((flag_get(&sa[320 + 31 - lane].w) ^ tag) & 1u) if (++it > SPIN_LIMIT) TRAP();
        STAMP(18);
        uint4 kv[11];
        uint32_t ok;
        do {
          ok = 0u;
#pragma unroll
          for (int v = 0; v < 11; v++) kv[v] = ll_ld128(sa + v * 32);
#pragma unroll
          for (int v = 0; v < 11; v++) ok |= kv[v].w ^ tag;
          if (++it > SPIN_LIMIT) TRAP();
        } while (__any_sync(~0u, ok & 1u));
        mbar_wait(bar(B_GEMM), 0);
#pragma unroll
        for (int v = 0; v < 11; v++) stsm4(kvl + 3 * CHB + v * 256, kv[v].x, kv[v].y, kv[v].z, kv[v].w & ~1u);
        fence_async_smem();
        __syncwarp();
        if (lane == 0) mbar_arrive(bar(B_KVN + 3));
      }
    }
    auto chunk = [&](int j) { return (SMD + (j < 4 ? j * CHB : KVO + (j - 4) * CHB)) >> 4; };
    const int dd = 16 * wl + gq - 2 * q4;
    bool redo = false;
  attention:
    {
    uint32_t ot[10][2];
    {
      float o[4][12], s[2][32]; uint32_t p[2][16];
      float inv[4][2];
      {
#pragma unroll
        for (int h = 0; h < 4; h++)
#pragma unroll
          for (int j = 0; j < 12; j++) o[h][j] = 0.f;
#pragma unroll 1
        for (int it = 0; it < 4; it++) {
          if (it == 2) {
            const uint32_t ca = opaque_u(chunk(wg + 4)), cb = opaque_u(m >= 2 ? chunk(wg) : chunk(wg + 4));
            uint32_t keep = m >= 2 ? ~0u : 0u;
            asm volatile("" : "+r"(keep));
            uint32_t mks[8];
#pragma unroll
            for (int k = 0; k < 8; k++) { mks[k] = (8 * k <= dd ? 0xffffu : 0u) | (8 * k + 1 <= dd ? 0xffff0000u : 0u); asm volatile("" : "+r"(mks[k])); }
            if (m >= 2) mbar_wait(bar(B_KVN + wg), 0);
            ASTAMP(36 + wg * 4 + it);
            wg_fence(); issue_qk(s[0], q[0], ca, 0); issue_qk(s[1], q[0], cb, 0); wg_commit();
#pragma unroll
            for (int h = 0; h < 4; h++) {
              wg_wait<0>(); reg_fence(s[0]); reg_fence(s[1]);
#pragma unroll
              for (int r = 0; r < 16; r++) {
                const int k = 2 * (r >> 2) + ((r >> 1) & 1) - (r & 1);
                if (k >= 0) { s[0][2 * r] = sel_le(8 * k, dd, s[0][2 * r], s[1][2 * r]); s[0][2 * r + 1] = sel_le(8 * k + 1, dd, s[0][2 * r + 1], s[1][2 * r + 1]); }
              }
              reg_fence(s[0]);
              if (h < 3) { wg_fence(); issue_qk(s[1], q[h + 1], cb, h + 1); }
#pragma unroll
              for (int r = 0; r < 16; r++) {
                const int k = 2 * (r >> 2) + ((r >> 1) & 1) - (r & 1);
                const uint32_t e = packbf(ex2(s[0][2 * r]), ex2(s[0][2 * r + 1]));
                const uint32_t mk = k < 0 ? ~0u : mks[k < 0 ? 0 : k];
                p[0][r] = e & mk; p[1][r] = e & ~mk & keep;
                if ((r & 3) == 3) { wg_fence(); if (r == 15 && h < 3) issue_qk(s[0], q[h + 1], ca, h + 1); issue_pv1(o[h], p[0], ca, h, r >> 2); issue_pv1(o[h], p[1], cb, h, r >> 2); }
              }
              wg_commit();
            }
          } else {
            const int j = it == 0 ? wg + 3 : it == 1 ? 2 * wg + 1 : 2;
            if (m * 2 + j < 4) continue;
            const uint32_t cb = chunk(j);
            mbar_wait(bar(j == 4 ? B_KV4 : B_KVN + j), 0);
            ASTAMP(36 + wg * 4 + it);
            wg_fence(); issue_qk(s[0], q[0], cb, 0); wg_commit();
#pragma unroll
            for (int h = 0; h < 4; h++) {
              if (h < 3) { wg_fence(); issue_qk(s[(h + 1) & 1], q[h + 1], cb, h + 1); wg_commit(); if (h == 0) wg_wait<1>(); else wg_wait<2>(); } else wg_wait<1>();
              reg_fence(s[h & 1]);
#pragma unroll
              for (int r = 0; r < 16; r++) {
                p[h & 1][r] = packbf(ex2(s[h & 1][2 * r]), ex2(s[h & 1][2 * r + 1]));
                if ((r & 3) == 3) { wg_fence(); issue_pv1(o[h], p[h & 1], cb, h, r >> 2); }
              }
              wg_commit();
            }
          }
          wg_wait<0>();
        }
      }
      uint32_t lmin = ~0u, lmax = 0u;
#pragma unroll
      for (int h = 0; h < 4; h++) {
        reg_fence(o[h]);
        const int src = (lane & ~3) | ((h & 1) ? 0 : 2);
        inv[h][0] = __shfl_sync(~0u, (h & 1) ? o[h][0] : o[h][8], src); inv[h][1] = __shfl_sync(~0u, (h & 1) ? o[h][2] : o[h][10], src);
        lmin = min(lmin, min(__float_as_uint(inv[h][0]), __float_as_uint(inv[h][1]))); lmax = max(lmax, max(__float_as_uint(inv[h][0]), __float_as_uint(inv[h][1])));
      }
      if (bar_or(2 + wg, 128, lmin < 0x21800000u || lmax > 0x5d800000u) && !redo) goto exact_max;
#pragma unroll
      for (int h = 0; h < 4; h++) { inv[h][0] = rcpf(inv[h][0]); inv[h][1] = rcpf(inv[h][1]); }
      if ((tid & 127) == 0) mbar_arrive(bar(B_ATT));
#pragma unroll
      for (int pr = 0; pr < 2; pr++) {
        const float (&oe)[12] = o[2 * pr]; const float (&oo)[12] = o[2 * pr + 1];
        const float e0 = inv[2 * pr][0], e1 = inv[2 * pr][1], f0 = inv[2 * pr + 1][0], f1 = inv[2 * pr + 1][1];
        ot[5 * pr][0] = packbf(oe[0] * e0, oe[1] * e0); ot[5 * pr][1] = packbf(oe[2] * e1, oe[3] * e1);
        ot[5 * pr + 1][0] = packbf(oe[4] * e0, oe[5] * e0); ot[5 * pr + 1][1] = packbf(oe[6] * e1, oe[7] * e1);
        ot[5 * pr + 2][0] = q4 < 2 ? packbf(oe[8] * e0, oe[9] * e0) : packbf(oo[0] * f0, oo[1] * f0);
        ot[5 * pr + 2][1] = q4 < 2 ? packbf(oe[10] * e1, oe[11] * e1) : packbf(oo[2] * f1, oo[3] * f1);
        ot[5 * pr + 3][0] = packbf(oo[4] * f0, oo[5] * f0); ot[5 * pr + 3][1] = packbf(oo[6] * f1, oo[7] * f1);
        ot[5 * pr + 4][0] = packbf(oo[8] * f0, oo[9] * f0); ot[5 * pr + 4][1] = packbf(oo[10] * f1, oo[11] * f1);
      }
    }
    uint32_t x2p[10][2], c1k, c2k;
    {
      uint4* ob = xch + m * (8 * 4096) + 2816 + warp * 160;
#pragma unroll
      for (int s = 0; s < 5; s++) { ot[2 * s + 1][1] = (ot[2 * s + 1][1] & ~1u) | (tag & 1u); ll_st128(ob + g * 4096 + s * 32, ot[2 * s][0], ot[2 * s][1], ot[2 * s + 1][0], ot[2 * s + 1][1]); asm volatile("and.b32 %0, %0, -2;" : "+r"(ot[2 * s + 1][1])); }
      STAMP(6 + wg);
      float acc[40];
#pragma unroll
      for (int i = 0; i < 40; i++) acc[i] = 0.f;
      mbar_wait(bar(B_WO), 0);
      if (wg == 0) STAMP(28);
      wg_fence();
#pragma unroll
      for (int s = 0; s < 5; s++) wg_rs80(acc, ot[2 * s][0], ot[2 * s][1], ot[2 * s + 1][0], ot[2 * s + 1][1], dsc(((SMD + WO) >> 4) + s * 32, 2560, 256, 3));
      wg_commit();
      const uint4* os[7];
#pragma unroll
      for (int j = 0; j < 7; j++) { os[j] = ob + ((g + j + 1) & 7) * 4096; asm volatile("" : "+l"(os[j])); }
      {
        const uint32_t* pw = &ob[(lane & 7) * 4096 + 159 - lane].w;
        int it = 0;
        while (__any_sync(~0u, (flag_get(pw) ^ tag) & 1u)) if (++it > SPIN_LIMIT) TRAP();
      }
      STAMP(29 + wg * 3);
      wg_wait<0>();
      uint4 af[7][5];
#pragma unroll
      for (int j = 0; j < 7; j++)
#pragma unroll
        for (int s = 0; s < 5; s++) af[j][s] = ll_ld128(os[j] + s * 32);
      if (wg == 0) STAMP(33);
#pragma unroll
      for (int j = 0; j < 7; j++) {
        int it = 0;
        while (__any_sync(~0u, ((af[j][0].w ^ tag) | (af[j][1].w ^ tag) | (af[j][2].w ^ tag) | (af[j][3].w ^ tag) | (af[j][4].w ^ tag)) & 1u)) {
#pragma unroll
          for (int s = 0; s < 5; s++) af[j][s] = ll_ld128(os[j] + s * 32);
          if (++it > SPIN_LIMIT) TRAP();
        }
#pragma unroll
        for (int s = 0; s < 5; s++) { af[j][s].w &= ~1u; asm volatile("" : "+r"(af[j][s].w)); }
        if (j == 0 && lane == 0) mbar_arrive(bar(B_OD));
        if (j == 6) { mbar_wait(bar(B_XR), 0); mbar_wait(bar(B_PRM2), 0); }
        if (wg == 0 && (j == 0 || j == 6)) ASTAMP(j == 0 ? 44 : 47);
        wg_fence();
#pragma unroll
        for (int s = 0; s < 5; s++) wg_rs80(acc, af[j][s].x, af[j][s].y, af[j][s].z, af[j][s].w, dsc(((SMD + (j < 6 ? WO + (j + 1) * 12800 : WO7)) >> 4) + s * 32, 2560, 256, 3));
        if (j == 3 || j == 6) wg_commit();
      }
      wg_wait<1>();
      const uint32_t xw = sm + T_XR + (warp * 16 + (lane & 15)) * 160 + (lane >> 4) * 16;
#pragma unroll
      for (int s = 0; s < 5; s++) { uint32_t r[4]; ldsm4(r, xw + s * 32); x2p[2 * s][0] = r[0]; x2p[2 * s][1] = r[1]; x2p[2 * s + 1][0] = r[2]; x2p[2 * s + 1][1] = r[3]; }
      uint4 ea[10];
#pragma unroll
      for (int t = 0; t < 10; t++) ea[t] = lds128(sm + T_EA + (gq & 1) * 640 + (t * 4 + q4) * 16);
      wg_wait<0>();
      reg_fence(acc);
      STAMP(8 + wg);
      float sa[4] = {0.f, 0.f, 0.f, 0.f}, sb[4] = {0.f, 0.f, 0.f, 0.f}, sc[4] = {0.f, 0.f, 0.f, 0.f}, sd[4] = {0.f, 0.f, 0.f, 0.f};
#pragma unroll
      for (int s = 0; s < 5; s++) {
#pragma unroll
        for (int t = 2 * s; t < 2 * s + 2; t++) {
          x2p[t][0] = hfma2(ea[t].x, packbf(acc[4 * t], acc[4 * t + 1]), x2p[t][0]);
          x2p[t][1] = hfma2(ea[t].x, packbf(acc[4 * t + 2], acc[4 * t + 3]), x2p[t][1]);
        }
        const uint32_t a0 = x2p[2 * s][0], a1 = x2p[2 * s][1], a2 = x2p[2 * s + 1][0], a3 = x2p[2 * s + 1][1];
        mma16f(sa, a0, a1, a2, a3, ea[2 * s].y, ea[2 * s + 1].y); mma16f(sb, a0, a1, a2, a3, ea[2 * s].z, ea[2 * s + 1].z);
        mma16f(sc, a0, a1, a2, a3, a0, a2); mma16f(sd, a0, a1, a2, a3, a1, a3);
      }
      if (q4 == (gq >> 1)) {
        uint4* pp = &g_part[cta * 128 + warp * 16 + gq * 2];
        ll_st128(pp, __float_as_uint(sa[0]), __float_as_uint((gq & 1) ? sc[1] : sc[0]), __float_as_uint(sa[1] + sb[1]), tag);
        ll_st128(pp + 1, __float_as_uint(sa[2]), __float_as_uint((gq & 1) ? sd[3] : sd[2]), __float_as_uint(sa[3] + sb[3]), tag);
      }
      if (wg == 0) STAMP(19);
      uint32_t rn0, rn1;
      {
        const uint4* pp = &g_part[(m * 8 + (q4 >> 1) * 4) * 128 + warp * 16 + gq * 2 + (q4 & 1)];
        uint4 w[4]; int it = 0;
        do {
          w[0] = ll_ld128(pp); w[1] = ll_ld128(pp + 128); w[2] = ll_ld128(pp + 256); w[3] = ll_ld128(pp + 384);
          if (++it > SPIN_LIMIT) TRAP();
        } while (w[0].w != tag || w[1].w != tag || w[2].w != tag || w[3].w != tag);
        float t1 = (__uint_as_float(w[0].x) + __uint_as_float(w[1].x)) + (__uint_as_float(w[2].x) + __uint_as_float(w[3].x));
        float t2 = (__uint_as_float(w[0].y) + __uint_as_float(w[1].y)) + (__uint_as_float(w[2].y) + __uint_as_float(w[3].y));
        float t3 = (__uint_as_float(w[0].z) + __uint_as_float(w[1].z)) + (__uint_as_float(w[2].z) + __uint_as_float(w[3].z));
        __syncwarp();
        t1 += __shfl_xor_sync(~0u, t1, 2); t2 += __shfl_xor_sync(~0u, t2, 2); t3 += __shfl_xor_sync(~0u, t3, 2);
        const float2 rc = lds64f(sm + T_SC);
        const float mean = t1 * (1.f / 640.f), rstd = rsqrtf(fmaxf(fmaf(-mean, mean, t2 * (1.f / 640.f)), 0.f) + 1e-5f);
        const uint32_t key = (sortable(fmaf(rstd, fmaf(-mean, rc.x, t3), rc.y)) & ~2047u) | (2047 - (m * 128 + warp * 16 + gq + (q4 & 1) * 8));
        STAMP(10 + wg);
        top2(key, 0u, c1k, c2k);
        if (lane == 0) sts64(sm + T_KEY + warp * 8, c1k, c2k);
        const uint32_t rn = packbf(rstd, -mean * bfround(rstd)), ro = __shfl_xor_sync(~0u, rn, 1);
        rn0 = (q4 & 1) ? ro : rn; rn1 = (q4 & 1) ? rn : ro;
      }
      bar_sync(1, 256);
      top2(lds32(sm + T_KEY + (lane & 15) * 4), 0u, c1k, c2k);
      if (wg == 0) STAMP(34);
      if (tid < 16) ll_st128(&g_keys[((g * 8 + (tid >> 1)) * 16 + m) * 2 + (tid & 1)], c1k, c2k, 0u, tag);
      const uint32_t rs0 = __byte_perm(rn0, 0, 0x1010), nm0 = __byte_perm(rn0, 0, 0x3232), rs1 = __byte_perm(rn1, 0, 0x1010), nm1 = __byte_perm(rn1, 0, 0x3232);
      uint32_t h2p[10][2], op[10][2];
#pragma unroll
      for (int t = 0; t < 10; t++) {
        const uint4 eb = lds128(sm + T_EB + (t * 4 + q4) * 16);
        h2p[t][0] = hfma2(hfma2(x2p[t][0], rs0, nm0), eb.x, eb.y); h2p[t][1] = hfma2(hfma2(x2p[t][1], rs1, nm1), eb.x, eb.y);
        op[t][0] = hfma2(eb.z, h2p[t][0], x2p[t][0]); op[t][1] = hfma2(eb.z, h2p[t][1], x2p[t][1]);
      }
#pragma unroll 1
      for (int cnd = 0; cnd < 2; cnd++) {
        const int lr = (2047 - (int)((cnd ? c2k : c1k) & 2047u)) & 127;
        if ((lr >> 4) == warp) {
          const bool hi = lr & 8; const int src = (lr & 7) * 4 + q4;
          const int base = ((m * 2 + cnd) * 8 + g) * 20 + q4;
#pragma unroll
          for (int s = 0; s < 5; s++) {
            const uint32_t a = __shfl_sync(~0u, hi ? h2p[2 * s][1] : h2p[2 * s][0], src), b = __shfl_sync(~0u, hi ? h2p[2 * s + 1][1] : h2p[2 * s + 1][0], src);
            ll_st128(&g_h2[gq * 5120 + base + s * 4], a, b, 0u, tag);
          }
          if (lane == src) {
#pragma unroll
            for (int s = 0; s < 5; s++) ll_st128(&g_x2[base + s * 4], hi ? x2p[2 * s][1] : x2p[2 * s][0], hi ? x2p[2 * s + 1][1] : x2p[2 * s + 1][0], 0u, tag);
          }
        }
      }
      __syncwarp();
#pragma unroll
      for (int s = 0; s < 5; s++) stsm4(xw + s * 32, op[2 * s][0], op[2 * s][1], op[2 * s + 1][0], op[2 * s + 1][1]);
      __syncwarp();
    }
    STAMP(12 + wg);
    mbar_wait(bar(B_MOEW), 0);
    uint32_t k1, k2; int r1, r2, sl1, sl2;
    const int kk = lane >> 3;
    auto winners = [&]() {
      uint4 w = make_uint4(0u, 0u, 0u, 0u);
      if (lane < 16) w = ll_wait128(&g_keys[((g * 8 + warp) * 16 + lane) * 2], tag);
      __syncwarp();
      top2(w.x, w.y, k1, k2);
      const uint32_t b1 = __ballot_sync(~0u, w.y == k1), b2 = __ballot_sync(~0u, w.y == k2);
      r1 = 2047 - (int)(k1 & 2047u); r2 = 2047 - (int)(k2 & 2047u);
      sl1 = (r1 >> 7) * 2 + (b1 ? 1 : 0); sl2 = (r2 >> 7) * 2 + (b2 ? 1 : 0);
      STAMP(14 + wg);
    };
    auto plain_rows = [&]() {
      __nv_bfloat16* ob = P.out + (m * 128 + warp * 16) * 640 + g * 80;
#pragma unroll
      for (int e = lane; e < 160; e += 32) {
        const int r = (e * 205) >> 11, row = m * 128 + warp * 16 + r;
        const uint4 v = lds128(sm + T_XR + warp * 2560 + e * 16);
        if (row != r1 && row != r2) *(uint4*)(ob + r * 560 + e * 8) = v;
      }
    };
    float d[2][4] = {{0.f, 0.f, 0.f, 0.f}, {0.f, 0.f, 0.f, 0.f}};
    const int wrow = (lane & 7) + (lane >> 4) * 8, whalf = (lane >> 3) & 1;
    auto red = [&]() {
      const bool u = q4 & 1, v = q4 & 2;
      float x[4];
#pragma unroll
      for (int i = 0; i < 4; i++) x[i] = (u ? d[1][i] : d[0][i]) + __shfl_xor_sync(~0u, u ? d[0][i] : d[1][i], 1);
      const float v0 = (v ? x[2] : x[0]) + __shfl_xor_sync(~0u, v ? x[0] : x[2], 2), v1 = (v ? x[3] : x[1]) + __shfl_xor_sync(~0u, v ? x[1] : x[3], 2);
      sts64(sm + T_MRED + warp * 256 + lane * 8, __float_as_uint(v0), __float_as_uint(v1));
      bar_sync(1, 256);
    };
    if (cta < 96) {
      uint32_t wf[10][4];
      const uint32_t wb = sm + MOEW + slab_off(warp * 80 + wrow, whalf);
#pragma unroll
      for (int s = 0; s < 10; s++) ldsm4t(wf[s], wb + (s >> 1) * 512 + (s & 1) * 20480);
      winners();
      const uint4* hp = &g_h2[g * 5120 + (((lane & 4) ? sl2 : sl1) * 8 + warp) * 20 + q4];
      uint4 a0, a1; int it = 0;
      do { a0 = ll_ld128(hp + kk * 4); a1 = ll_ld128(hp + 16); if (++it > SPIN_LIMIT) TRAP(); } while (a0.w != tag || a1.w != tag);
      __syncwarp();
      if (wg == 0) ASTAMP(45);
#pragma unroll
      for (int s = 0; s < 5; s++) {
        const bool on = s < 4 ? kk == s : kk == 0;
        const uint32_t x = on ? (s < 4 ? a0.x : a1.x) : 0u, y = on ? (s < 4 ? a0.y : a1.y) : 0u;
        mma16f(d[0], wf[2 * s][0], wf[2 * s][1], wf[2 * s][2], wf[2 * s][3], x, y); mma16f(d[1], wf[2 * s + 1][0], wf[2 * s + 1][1], wf[2 * s + 1][2], wf[2 * s + 1][3], x, y);
      }
      red();
      if (warp == 0) {
        float v0 = 0.f, v1 = 0.f;
#pragma unroll
        for (int w2 = 0; w2 < 8; w2++) { const float2 t = lds64f(sm + T_MRED + w2 * 256 + lane * 8); v0 += t.x; v1 += t.y; }
        v0 = bfround(v0); v1 = bfround(v1);
        const float u0 = __shfl_xor_sync(~0u, v0, 1), u1 = __shfl_xor_sync(~0u, v1, 1);
        const uint32_t gu = packbf(bfround(silu_f(v0)) * u0, bfround(silu_f(v1)) * u1), sel = (lane & 4) ? 0x7632u : 0x5410u;
        const uint32_t gu1 = __byte_perm(__shfl_sync(~0u, gu, q4 * 8), __shfl_sync(~0u, gu, q4 * 8 + 4), sel), gu2 = __byte_perm(__shfl_sync(~0u, gu, q4 * 8 + 2), __shfl_sync(~0u, gu, q4 * 8 + 6), sel);
        ll_st128(&g_gu[kk * 768 + cta * 8 + (lane & 7)], gu1, gu2, 0u, tag);
        STAMP(46);
      }
      plain_rows();
    } else {
      uint32_t wf[12][4], wt[12][4];
      const uint32_t wb = sm + MOEW + (warp * 192 + wrow) * 48 + whalf * 16;
#pragma unroll
      for (int s = 0; s < 12; s++) { ldsm4t(wf[s], wb + s * 768); ldsm4t(wt[s], wb + s * 768 + 32); }
      const int j = cta - 96, tk = tid >= 10, pl = tid - tk * 10;
      uint32_t fh = 0, fx = 0, fg = 0;
      if (tid < 20) fg = ll_wait64(&g_mod[1600 + j * 10 + pl], tag);
      __syncwarp();
      winners();
      plain_rows();
      const uint32_t kx = tk ? k2 : k1;
      const float sg = bfround(rcpf(1.f + ex2(-1.4426950408889634f * bfround(unsortable((kx & ~2047u) | 1024u)))));
      if (tid < 20) {
        const int pi = (j & 3) * 10 + pl, t = pi >> 2;
        const int ix = ((tk ? sl2 : sl1) * 8 + (j >> 2)) * 20 + (t >> 1) * 4 + (pi & 3);
        uint4 wh, wx; int it = 0;
        do { wh = ll_ld128(&g_h2[g * 5120 + ix]); wx = ll_ld128(&g_x2[ix]); if (++it > SPIN_LIMIT) TRAP(); } while (wh.w != tag || wx.w != tag);
        fh = (t & 1) ? wh.y : wh.x; fx = (t & 1) ? wx.y : wx.x;
      }
      __syncwarp();
      const uint4* gp = &g_gu[(cta & 3) * 768 + (warp * 12 + kk) * 8 + (lane & 7)];
      uint4 a[3]; int it = 0;
      do { a[0] = ll_ld128(gp); a[1] = ll_ld128(gp + 32); a[2] = ll_ld128(gp + 64); if (++it > SPIN_LIMIT) TRAP(); } while (a[0].w != tag || a[1].w != tag || a[2].w != tag);
      __syncwarp();
      if (wg == 0) STAMP(46);
#pragma unroll
      for (int s = 0; s < 12; s++) {
        const bool on = kk == (s & 3);
        const uint32_t x = on ? a[s >> 2].x : 0u, y = on ? a[s >> 2].y : 0u;
        mma16f(d[0], wf[s][0], wf[s][1], wf[s][2], wf[s][3], x, y); mma16f(d[1], wt[s][0], wt[s][1], wt[s][2], wt[s][3], x, y);
      }
      red();
      if (tid < 20) {
        const int c0 = 2 * pl + (j & 1) * 4;
        const uint32_t ad = sm + T_MRED + ((c0 & 7) * 4 + ((c0 >> 3) & 1) * 2 + (c0 >> 4)) * 8 + tk * 4;
        float v0 = 0.f, v1 = 0.f;
#pragma unroll
        for (int w2 = 0; w2 < 8; w2++) { v0 += lds32f(ad + w2 * 256); v1 += lds32f(ad + w2 * 256 + 32); }
        const uint32_t y = packbf(bfround(v0) * sg, bfround(v1) * sg);
        *(uint32_t*)(P.out + (tk ? r2 : r1) * 640 + j * 20 + pl * 2) = hfma2(fg, hadd2(fh, y), fx);
      }
    }
    if (cta == 0 && tid < 8) asm volatile("st.relaxed.gpu.global.u32 [%0], %1;" ::"l"(&g_epoch[tid * 32]), "r"(tag) : "memory");
    STAMP(16 + wg);
    return;
    }
  exact_max:
    {
      uint32_t qq[4][8];
#pragma unroll
      for (int h = 0; h < 4; h++)
#pragma unroll
        for (int i = 0; i < 8; i++) qq[h][i] = q[h][i];
      exact_row_max(qq, sm, wg, m, dd);
#pragma unroll
      for (int h = 0; h < 4; h++) { q[h][6] = qq[h][6]; q[h][7] = qq[h][7]; }
      redo = true;
      goto attention;
    }
  } else {
    asm volatile("setmaxnreg.dec.sync.aligned.u32 40;");
    asm volatile("bar.arrive 0, 384;" ::: "memory");
    if (warp == 8) asm volatile("bar.arrive 5, 128;" ::: "memory");
    else { bar_sync(5, 128); tag = lds32(sm + T_TAG); }
    if (warp == 8) {
      if (lane == 0) {
#pragma unroll 1
        for (int c = 0; c < 10; c++) {
          const int s = c & 3; const uint32_t st = sm + s * STAGE;
          if (c == TMAFIRST) mbar_wait(bar(B_C1), 0);
          if (c >= 4) mbar_wait(bar(B_EMPTY + s), ((c >> 2) & 1) ^ 1);
          mbar_expect_tx(bar(B_FULL + s), STAGE);
          tma2d(st, &P.mx, c * 64, m * 128, bar(B_FULL + s));
          tma3d(st + 16384, &P.mw64, g * 80, c * 64, 0, bar(B_FULL + s));
          tma3d(st + 40960, &P.mw16, g * 80 + 64, c * 64, 0, bar(B_FULL + s));
        }
      }
      if (lane >= 1 && lane <= 5) { const void* d = lane == 1 ? &P.mwo : lane == 2 ? &P.mxr : lane == 3 ? &P.mwg : lane == 4 ? &P.mwu : &P.mwd; asm volatile("prefetch.tensormap [%0];" ::"l"(d) : "memory"); }
      __syncwarp();
      STAMP(26);
    } else {
      mbar_wait(bar(B_C1), 0);
      aux_mod(P, sm, tag);
    }
    mbar_wait(bar(AUXGO), 0);
    tag = lds32(sm + T_TAG);
    if (m > 0) {
      const uint4* src = g_xch + (cta - 16) * 4096 + (warp & 3) * 352 + lane;
      const uint32_t kvl = sm + (warp & 3) * (2 * GB) + ((lane >> 3) & 1) * GB + (lane >> 4) * 128 + (lane & 7) * 16;
      int it = 0;
      {
        const int j = m > 1 ? min(lane, 2) : 2;
        const uint32_t* pw = &src[(j >> 1) * (8 * 4096) + (j & 1) * 1408 + 320 + 31 - lane].w;
        while (__any_sync(~0u, (flag_get(pw) ^ tag) & 1u)) if (++it > SPIN_LIMIT) TRAP();
      }
      mbar_wait(bar(B_GEMM), 0);
#pragma unroll 1
      for (int i = m > 1 ? 0 : 4; i < 6; i++) {
        const int j = i < 4 ? 1 - (i >> 1) : 2, v0 = (i & 1) * 5;
        const uint4* sp = src + (j >> 1) * (8 * 4096) + (j & 1) * 1408 + v0 * 32;
        uint4 kv[6];
        uint32_t ok;
        do {
          ok = 0u;
#pragma unroll
          for (int v = 0; v < 6; v++) kv[v] = ll_ld128(sp + v * 32);
#pragma unroll
          for (int v = 0; v < 6; v++) ok |= kv[v].w ^ tag;
          if (++it > SPIN_LIMIT) TRAP();
        } while (__any_sync(~0u, ok & 1u));
#pragma unroll
        for (int v = 0; v < 6; v++) stsm4(kvl + j * CHB + (v0 + v) * 256, kv[v].x, kv[v].y, kv[v].z, kv[v].w & ~1u);
        if (i & 1) {
          fence_async_smem();
          __syncwarp();
          if (lane == 0) mbar_arrive(bar(B_KVN + j));
        }
      }
      STAMP(27);
    }
    aux_late(P, sm, tag);
  }
}

typedef CUresult (*EncFn)(CUtensorMap*, CUtensorMapDataType, cuuint32_t, void*, const cuuint64_t*, const cuuint64_t*, const cuuint32_t*, const cuuint32_t*, CUtensorMapInterleave, CUtensorMapSwizzle, CUtensorMapL2promotion, CUtensorMapFloatOOBfill);
static void make_map(EncFn enc, CUtensorMap* mp, const void* ptr, int rank, const cuuint64_t* dims, const cuuint64_t* strides, const cuuint32_t* box, CUtensorMapSwizzle sw) {
  const cuuint32_t es[3] = {1, 1, 1};
  enc(mp, CU_TENSOR_MAP_DATA_TYPE_BFLOAT16, rank, (void*)ptr, dims, strides, box, es, CU_TENSOR_MAP_INTERLEAVE_NONE, sw, CU_TENSOR_MAP_L2_PROMOTION_L2_128B, CU_TENSOR_MAP_FLOAT_OOB_FILL_NONE);
}
extern "C" void kernel_launch(void* const* d_in, const int* in_sizes, int n_in, void* d_out, int out_size) {
  void* fn = nullptr; cudaDriverEntryPointQueryResult qr;
  cudaGetDriverEntryPoint("cuTensorMapEncodeTiled", &fn, cudaEnableDefault, &qr);
  EncFn enc = (EncFn)fn;
  Params P;
  P.x = (const __nv_bfloat16*)d_in[0]; P.wqkv = (const __nv_bfloat16*)d_in[1]; P.wo = (const __nv_bfloat16*)d_in[2];
  P.wr = (const __nv_bfloat16*)d_in[4]; P.wg = (const __nv_bfloat16*)d_in[5]; P.wu = (const __nv_bfloat16*)d_in[6]; P.wd = (const __nv_bfloat16*)d_in[7];
  P.c = (const __nv_bfloat16*)d_in[8]; P.wmod = (const __nv_bfloat16*)d_in[9]; P.out = (__nv_bfloat16*)d_out;
  { const cuuint64_t d[2] = {640, 2048}, s[1] = {1280}; const cuuint32_t b[2] = {64, 128}; make_map(enc, &P.mx, P.x, 2, d, s, b, CU_TENSOR_MAP_SWIZZLE_128B); }
  { const cuuint64_t d[3] = {640, 640, 3}, s[2] = {3840, 1280}; const cuuint32_t b[3] = {64, 64, 3}; make_map(enc, &P.mw64, P.wqkv, 3, d, s, b, CU_TENSOR_MAP_SWIZZLE_128B); }
  { const cuuint64_t d[3] = {640, 640, 3}, s[2] = {3840, 1280}; const cuuint32_t b[3] = {16, 64, 3}; make_map(enc, &P.mw16, P.wqkv, 3, d, s, b, CU_TENSOR_MAP_SWIZZLE_32B); }
  { const cuuint64_t d[3] = {16, 640, 40}, s[2] = {1280, 32}; const cuuint32_t b[3] = {16, 80, 5}; make_map(enc, &P.mwo, P.wo, 3, d, s, b, CU_TENSOR_MAP_SWIZZLE_32B); }
  { const cuuint64_t d[2] = {640, 2048}, s[1] = {1280}; const cuuint32_t b[2] = {80, 128}; make_map(enc, &P.mxr, P.x, 2, d, s, b, CU_TENSOR_MAP_SWIZZLE_NONE); }
  { const cuuint64_t d[2] = {1536, 640}, s[1] = {3072}; const cuuint32_t b[2] = {16, 160}; make_map(enc, &P.mwg, P.wg, 2, d, s, b, CU_TENSOR_MAP_SWIZZLE_32B); make_map(enc, &P.mwu, P.wu, 2, d, s, b, CU_TENSOR_MAP_SWIZZLE_32B); }
  { const cuuint64_t d[2] = {640, 1536}, s[1] = {1280}; const cuuint32_t b[2] = {24, 256}; make_map(enc, &P.mwd, P.wd, 2, d, s, b, CU_TENSOR_MAP_SWIZZLE_NONE); }
  cudaFuncSetAttribute(fused_kernel, cudaFuncAttributeMaxDynamicSharedMemorySize, SMEM_BYTES);
  fused_kernel<<<128, 384, SMEM_BYTES>>>(P.x, P.wmod, P.c, P);
}
```
